```python
import torch

def _softmax(x, axis=-1):
    return torch.softmax(x, dim=axis)
def _gelu(x):
    return torch.nn.functional.gelu(x, approximate="tanh")
def _silu(x):
    return torch.nn.functional.silu(x)
def _sigmoid(x):
    return torch.sigmoid(x)
def _layernorm(x, axis=-1, eps=1e-5):
    m = x.mean(dim=axis, keepdim=True)
    v = x.var(dim=axis, keepdim=True, unbiased=False)
    return (x - m) / torch.sqrt(v + eps)
def _scatter_add(tgt, idx, src, axis=0):
    return tgt.clone().index_add_(axis, idx, src)
def _segment_sum(src, seg, n):
    out = torch.zeros((n,) + src.shape[1:], dtype=src.dtype)
    return out.index_add_(0, seg, src)
def _pad(x, pw):
    flat = tuple(v for pair in reversed(pw) for v in pair)
    return torch.nn.functional.pad(x, flat)

kernel_name = 'gated_mix__ssm_conv_h3__geglu_ffn__prompt'

def setup_inputs():

    _w = (lambda a: (lambda t: t.to(torch.bfloat16) if t.is_floating_point() else t)(torch.as_tensor(a)))
    def _A_setup():
        B, S, D = 1, 2048, 512
        ks = 4
        return {
            "q": _w((lambda *s: torch.randn(*s, dtype=torch.bfloat16) * 0.05)(B, S, D)),
            "k": _w((lambda *s: torch.randn(*s, dtype=torch.bfloat16) * 0.2)(B, S, D)),
            "v": _w((lambda *s: torch.randn(*s, dtype=torch.bfloat16) * 0.2)(B, S, D)),
            "shift_k": _w((lambda *s: torch.randn(*s, dtype=torch.bfloat16) * 0.2)(D, ks) * 0.5),
            "ssm_k": _w((lambda *s: torch.randn(*s, dtype=torch.bfloat16) * 0.8)(D, S) * (1.0 / S ** 0.5)),
            "ssm_D": _w((lambda *s: torch.randn(*s, dtype=torch.bfloat16) * 0.2)(D)),
        }
    _A_in = _A_setup()

    def _B_setup():
        B, S, D, F = 1, 2048, 512, 1792
        return {
            "x": _w((lambda *s: torch.randn(*s, dtype=torch.bfloat16) * 0.05)(B, S, D)),
            "w_gate": _w((lambda *s: torch.randn(*s, dtype=torch.bfloat16) * 0.05)(D, F)),
            "w_up": _w((lambda *s: torch.randn(*s, dtype=torch.bfloat16) * 0.05)(D, F)),
            "w_down": _w((lambda *s: torch.randn(*s, dtype=torch.bfloat16) * 0.05)(F, D)),
        }
    _B_in = _B_setup()

    return {
        "A_q": _A_in["q"],
        "A_k": _A_in["k"],
        "A_v": _A_in["v"],
        "A_shift_k": _A_in["shift_k"],
        "A_ssm_k": _A_in["ssm_k"],
        "A_ssm_D": _A_in["ssm_D"],
        "B_x": _B_in["x"],
        "B_w_gate": _B_in["w_gate"],
        "B_w_up": _B_in["w_up"],
        "B_w_down": _B_in["w_down"],
        "gate_w": _w((lambda *s: torch.randn(*s, dtype=torch.bfloat16) * 0.05)(512) * 16.0),
    }

def reference(A_q, A_k, A_v, A_shift_k, A_ssm_k, A_ssm_D, B_x, B_w_gate, B_w_up, B_w_down, gate_w):
    def _A_ref(q, k, v, shift_k, ssm_k, ssm_D):
        B, S, D = q.shape
        ks = shift_k.shape[-1]
        k_pad = _pad(k, ((0, 0), (ks - 1, 0), (0, 0)))
        k_shift = torch.zeros_like(k)
        for t in range(ks):
            k_shift = k_shift + k_pad[:, t:t + S, :] * shift_k[:, ks - 1 - t][None, None, :]
        kv = k_shift * v
        L = 2 * S
        kv_pad = _pad(kv, ((0, 0), (0, S), (0, 0)))
        kf_pad = _pad(ssm_k, ((0, 0), (0, S)))
        kv_f = (lambda x, axes=(-2,-1): torch.fft.rfft2(x.float(), dim=axes))(kv_pad[:, None, :, :], axes=(1, 2))
        kf_f = (lambda x, axes=(-2,-1): torch.fft.rfft2(x.float(), dim=axes))(kf_pad[:, None, :], axes=(1, 2))
        kf_f = (lambda x, *d: x.permute(*d))(kf_f, 1, 2, 0)
        y_f = kv_f * kf_f[None, :, :, :]
        y = (lambda x, s, axes=(-2,-1): torch.fft.irfft2(x, s=s, dim=axes).to(torch.bfloat16))(y_f, (1, L), axes=(1, 2))[:, 0, :S, :]
        y = y + kv * ssm_D[None, None, :]
        return q * y

    def _B_ref(x, w_gate, w_up, w_down):
        return (_gelu(x @ w_gate) * (x @ w_up)) @ w_down

    x = A_q
    g = _sigmoid((x * gate_w).sum(-1, keepdims=True))
    a = _A_ref(x, A_k, A_v, A_shift_k, A_ssm_k, A_ssm_D)
    b = _B_ref(x, B_w_gate, B_w_up, B_w_down)
    return g * a + (1 - g) * b
```

```cpp
#include <cuda_runtime.h>
#include <cuda_bf16.h>
#include <cuda.h>
#include <stdint.h>

namespace {

constexpr int S_LEN = 2048, D_DIM = 512, F_DIM = 1792;
constexpr int NCTA = 128;

__device__ __align__(1024) __nv_bfloat16 g_h[S_LEN * F_DIM];
__device__ __align__(1024) __nv_bfloat16 g_kvT[D_DIM * S_LEN];
__device__ __align__(1024) __nv_bfloat16 g_zT[D_DIM * S_LEN];
__device__ __align__(1024) float g_gate[S_LEN];
constexpr int FL_KV = 0, FL_Z = 8, FL_G = 16, FL_A = 32, FL_B = 48, FL_DONE = 64, FL_COUNT = 65;
__device__ __align__(1024) unsigned int g_flags[FL_COUNT * 8];

constexpr uint32_t OFF_W = 131072;
constexpr uint32_t SLOT2 = 32768, NSLOT2 = 6;
constexpr uint32_t U_PLANE = 2176, U_BUF = 4352, U_PAD = 128;
constexpr uint32_t OFF_RED = 196608;
constexpr uint32_t OFF_PR = OFF_RED + 16384;
constexpr uint32_t OFF_U = OFF_PR + 8320;
constexpr uint32_t OFF_GA = OFF_PR;
constexpr uint32_t OFF_G2 = OFF_U + 2 * U_BUF;
constexpr uint32_t OFF_BAR = OFF_G2 + 256;
constexpr uint32_t SMEM_BYTES = OFF_BAR + 448;
constexpr uint32_t OFF_CU0 = 65536, OFF_CU1 = OFF_CU0 + U_BUF, OFF_CPR0 = OFF_CU1 + U_BUF, OFF_CPR1 = OFF_CPR0 + 8320;
constexpr uint32_t OFF_CRED0 = 98304, OFF_CRED1 = 114688;
constexpr uint32_t OFF_XCHG = 4 * SLOT2;
constexpr uint32_t OFF_OST = 5 * SLOT2 + 16384;
static_assert(SMEM_BYTES <= 232448, "smem");

#define PF_KV 300
#define PF_W 3000
#define PF_H 5000
#define PF_WD 8000
#define MAPV 0
constexpr int SPIN_LIMIT = 1 << 18;
#define TR(i)
#define TRX(i)
#define TC(i)

__device__ __forceinline__ uint32_t smem_u32(const void* p) { return (uint32_t)__cvta_generic_to_shared(p); }
__device__ __forceinline__ uint64_t make_desc(uint32_t addr, uint32_t lbo, uint32_t sbo, uint32_t swz) {
  return (uint64_t)((addr & 0x3FFFF) >> 4) | ((uint64_t)(lbo >> 4) << 16) | ((uint64_t)(sbo >> 4) << 32) | ((uint64_t)swz << 62);
}
__device__ __forceinline__ void wg_fence() { asm volatile("wgmma.fence.sync.aligned;" ::: "memory"); }
__device__ __forceinline__ void wg_commit() { asm volatile("wgmma.commit_group.sync.aligned;" ::: "memory"); }
template <int N> __device__ __forceinline__ void wg_wait() { asm volatile("wgmma.wait_group.sync.aligned %0;" ::"n"(N) : "memory"); }
__device__ __forceinline__ void mbar_init(uint32_t bar, int cnt) { asm volatile("mbarrier.init.shared::cta.b64 [%0], %1;" ::"r"(bar), "r"(cnt) : "memory"); }
__device__ __forceinline__ void mbar_expect_tx(uint32_t bar, uint32_t bytes) {
  asm volatile("mbarrier.arrive.expect_tx.shared::cta.b64 _, [%0], %1;" ::"r"(bar), "r"(bytes) : "memory");
}
__device__ __forceinline__ void mbar_arrive(uint32_t bar) { asm volatile("mbarrier.arrive.shared::cta.b64 _, [%0];" ::"r"(bar) : "memory"); }
__device__ __forceinline__ void mbar_wait(uint32_t bar, uint32_t parity) {
  uint32_t ok;
  int it = 0;
  do {
    asm volatile("{\n.reg .pred p;\nmbarrier.try_wait.parity.shared::cta.b64 p, [%1], %2;\nselp.u32 %0, 1, 0, p;\n}\n"
                 : "=r"(ok) : "r"(bar), "r"(parity) : "memory");
  } while (!ok && ++it < SPIN_LIMIT);
}
__device__ __forceinline__ void bar_sync(int id, int n) { asm volatile("bar.sync %0, %1;" ::"r"(id), "r"(n) : "memory"); }
__device__ __forceinline__ void bar_arrive(int id, int n) { asm volatile("bar.arrive %0, %1;" ::"r"(id), "r"(n) : "memory"); }
__device__ __forceinline__ void fence_async_smem() { asm volatile("fence.proxy.async.shared::cta;" ::: "memory"); }
__device__ __forceinline__ void fence_async_all() { asm volatile("fence.proxy.async.global;" ::: "memory"); }
__device__ __forceinline__ void tma_2d(uint32_t dst, const CUtensorMap* m, int c0, int c1, uint32_t bar) {
  asm volatile("cp.async.bulk.tensor.2d.shared::cluster.global.mbarrier::complete_tx::bytes [%0], [%1, {%3, %4}], [%2];"
               ::"r"(dst), "l"(m), "r"(bar), "r"(c0), "r"(c1) : "memory");
}
__device__ __forceinline__ void tma_3d(uint32_t dst, const CUtensorMap* m, int c0, int c1, int c2, uint32_t bar) {
  asm volatile("cp.async.bulk.tensor.3d.shared::cluster.global.mbarrier::complete_tx::bytes [%0], [%1, {%3, %4, %5}], [%2];"
               ::"r"(dst), "l"(m), "r"(bar), "r"(c0), "r"(c1), "r"(c2) : "memory");
}
__device__ __forceinline__ void tma_5d(uint32_t dst, const CUtensorMap* m, int c0, int c4, uint32_t bar) {
  asm volatile("cp.async.bulk.tensor.5d.shared::cluster.global.mbarrier::complete_tx::bytes [%0], [%1, {%3, %4, %4, %4, %5}], [%2];"
               ::"r"(dst), "l"(m), "r"(bar), "r"(c0), "r"(0), "r"(c4) : "memory");
}
__device__ __forceinline__ void tma_store_2d(const CUtensorMap* m, uint32_t src, int c0, int c1) {
  asm volatile("cp.async.bulk.tensor.2d.global.shared::cta.bulk_group [%0, {%2, %3}], [%1];" ::"l"(m), "r"(src), "r"(c0), "r"(c1) : "memory");
}
__device__ __forceinline__ void bulk_g2s(uint32_t dst, const void* src, uint32_t bytes, uint32_t bar) {
  asm volatile("cp.async.bulk.shared::cluster.global.mbarrier::complete_tx::bytes [%0], [%1], %2, [%3];"
               ::"r"(dst), "l"(src), "r"(bytes), "r"(bar) : "memory");
}
__device__ __forceinline__ void prefetch_l2(const void* src, uint32_t bytes) {
  asm volatile("cp.async.bulk.prefetch.L2.global [%0], %1;" ::"l"(src), "r"(bytes) : "memory");
}
__device__ __forceinline__ void prefetch_tma_2d(const CUtensorMap* m, int c0, int c1) {
  asm volatile("cp.async.bulk.prefetch.tensor.2d.L2.global [%0, {%1, %2}];" ::"l"(m), "r"(c0), "r"(c1) : "memory");
}
__device__ __forceinline__ uint32_t mapa(uint32_t addr, uint32_t rank) {
  uint32_t r; asm volatile("mapa.shared::cluster.u32 %0, %1, %2;" : "=r"(r) : "r"(addr), "r"(rank)); return r;
}
__device__ __forceinline__ void mbar_arrive_remote(uint32_t bar) {
  asm volatile("mbarrier.arrive.relaxed.cluster.shared::cluster.b64 _, [%0];" ::"r"(bar) : "memory");
}
__device__ __forceinline__ void mbar_wait_cluster(uint32_t bar, uint32_t parity) {
  uint32_t ok;
  int it = 0;
  do {
    asm volatile("{\n.reg .pred p;\nmbarrier.try_wait.parity.acquire.cluster.shared::cta.b64 p, [%1], %2;\nselp.u32 %0, 1, 0, p;\n}\n"
                 : "=r"(ok) : "r"(bar), "r"(parity) : "memory");
  } while (!ok && ++it < SPIN_LIMIT);
}
__device__ __forceinline__ void st_async_v4(uint32_t addr, float x, float y, float z, float w, uint32_t bar) {
  asm volatile("st.async.weak.shared::cluster.mbarrier::complete_tx::bytes.v4.f32 [%0], {%1,%2,%3,%4}, [%5];"
               ::"r"(addr), "f"(x), "f"(y), "f"(z), "f"(w), "r"(bar) : "memory");
}
__device__ __forceinline__ void st_async_v4u(uint32_t addr, const uint4& v, uint32_t bar) {
  asm volatile("st.async.weak.shared::cluster.mbarrier::complete_tx::bytes.v4.b32 [%0], {%1,%2,%3,%4}, [%5];"
               ::"r"(addr), "r"(v.x), "r"(v.y), "r"(v.z), "r"(v.w), "r"(bar) : "memory");
}
__device__ __forceinline__ void fence_gpu() { asm volatile("fence.acq_rel.gpu;" ::: "memory"); }
__device__ __forceinline__ void prefetch_tmap(const CUtensorMap* m) { asm volatile("prefetch.tensormap [%0];" ::"l"(m) : "memory"); }
__device__ __forceinline__ void flag_add(int idx) {
  asm volatile("red.release.gpu.global.add.u32 [%0], 1;" ::"l"(&g_flags[idx * 8]) : "memory");
}
__device__ __forceinline__ void flag_add_relaxed(int idx) {
  asm volatile("red.relaxed.gpu.global.add.u32 [%0], 1;" ::"l"(&g_flags[idx * 8]) : "memory");
}
__device__ __forceinline__ void flag_wait(int idx, unsigned target) {
  unsigned v;
  int it = 0;
  while (true) {
    asm volatile("ld.acquire.gpu.global.u32 %0, [%1];" : "=r"(v) : "l"(&g_flags[idx * 8]) : "memory");
    if (v >= target || ++it > SPIN_LIMIT) break;
    __nanosleep(32);
  }
}
__device__ __forceinline__ void ldsm_x4_t(uint32_t& r0, uint32_t& r1, uint32_t& r2, uint32_t& r3, uint32_t addr) {
  asm volatile("ldmatrix.sync.aligned.m8n8.x4.trans.shared.b16 {%0,%1,%2,%3}, [%4];" : "=r"(r0), "=r"(r1), "=r"(r2), "=r"(r3) : "r"(addr) : "memory");
}
__device__ __forceinline__ void ldsm_x4(uint32_t& r0, uint32_t& r1, uint32_t& r2, uint32_t& r3, uint32_t addr) {
  asm volatile("ldmatrix.sync.aligned.m8n8.x4.shared.b16 {%0,%1,%2,%3}, [%4];" : "=r"(r0), "=r"(r1), "=r"(r2), "=r"(r3) : "r"(addr) : "memory");
}
__device__ __forceinline__ void stsm_x4_t(uint32_t addr, uint32_t r0, uint32_t r1, uint32_t r2, uint32_t r3) {
  asm volatile("stmatrix.sync.aligned.m8n8.x4.trans.shared.b16 [%0], {%1,%2,%3,%4};" ::"r"(addr), "r"(r0), "r"(r1), "r"(r2), "r"(r3) : "memory");
}
__device__ __forceinline__ uint32_t lds32(uint32_t a) { uint32_t v; asm volatile("ld.shared.u32 %0, [%1];" : "=r"(v) : "r"(a) : "memory"); return v; }
__device__ __forceinline__ uint32_t lds32v(uint32_t a) { uint32_t v; asm volatile("ld.volatile.shared.u32 %0, [%1];" : "=r"(v) : "r"(a) : "memory"); return v; }
__device__ __forceinline__ uint4 lds128(uint32_t a) {
  uint4 v; asm volatile("ld.shared.v4.u32 {%0,%1,%2,%3}, [%4];" : "=r"(v.x), "=r"(v.y), "=r"(v.z), "=r"(v.w) : "r"(a) : "memory"); return v;
}
__device__ __forceinline__ float4 lds128f(uint32_t a) {
  float4 v; asm volatile("ld.shared.v4.f32 {%0,%1,%2,%3}, [%4];" : "=f"(v.x), "=f"(v.y), "=f"(v.z), "=f"(v.w) : "r"(a) : "memory"); return v;
}
__device__ __forceinline__ void sts32(uint32_t a, uint32_t v) { asm volatile("st.shared.u32 [%0], %1;" ::"r"(a), "r"(v) : "memory"); }
__device__ __forceinline__ void sts128(uint32_t a, uint32_t x, uint32_t y, uint32_t z, uint32_t w) {
  asm volatile("st.shared.v4.u32 [%0], {%1,%2,%3,%4};" ::"r"(a), "r"(x), "r"(y), "r"(z), "r"(w) : "memory");
}
__device__ __forceinline__ void sts128f(uint32_t a, float x, float y, float z, float w) {
  asm volatile("st.shared.v4.f32 [%0], {%1,%2,%3,%4};" ::"r"(a), "f"(x), "f"(y), "f"(z), "f"(w) : "memory");
}
__device__ __forceinline__ uint32_t bf2_bits(__nv_bfloat162 v) { return *reinterpret_cast<uint32_t*>(&v); }
__device__ __forceinline__ __nv_bfloat162 bits_bf2(uint32_t v) { return *reinterpret_cast<__nv_bfloat162*>(&v); }
__device__ __forceinline__ uint32_t mul2(uint32_t a, uint32_t b) { return bf2_bits(__hmul2_rn(bits_bf2(a), bits_bf2(b))); }
__device__ __forceinline__ uint32_t add2(uint32_t a, uint32_t b) { return bf2_bits(__hadd2_rn(bits_bf2(a), bits_bf2(b))); }
__device__ __forceinline__ uint32_t pack2(float lo, float hi) { return bf2_bits(__floats2bfloat162_rn(lo, hi)); }
__device__ __forceinline__ float lo_f(uint32_t v) { return __uint_as_float(v << 16); }
__device__ __forceinline__ float hi_f(uint32_t v) { return __uint_as_float(v & 0xffff0000u); }
__device__ __forceinline__ float tanh_fast(float x) { float y; asm("tanh.approx.f32 %0, %1;" : "=f"(y) : "f"(x)); return y; }
__device__ __forceinline__ float gelu_tanh(float a) {
  float t = tanh_fast(a * fmaf(0.035677408136f, a * a, 0.7978845608f));
  float h = 0.5f * a;
  return fmaf(h, t, h);
}
__device__ __forceinline__ uint32_t geglu2(float g0, float g1, float u0, float u1) {
  uint32_t gb = pack2(g0, g1);
  uint32_t ub = pack2(u0, u1);
  uint32_t gl = pack2(gelu_tanh(lo_f(gb)), gelu_tanh(hi_f(gb)));
  return mul2(gl, ub);
}

template<int TA, int TB, int OA, int OB> __device__ __forceinline__ void wgmma_ss_n64(float* d, uint64_t da, uint64_t db, int scaleD) {
  asm volatile("{\n.reg .pred p;\n.reg .b64 ta, tb;\nsetp.ne.b32 p, %34, 0;\nadd.s64 ta, %32, %37;\nadd.s64 tb, %33, %38;\n"
    "wgmma.mma_async.sync.aligned.m64n64k16.f32.bf16.bf16 {%0, %1, %2, %3, %4, %5, %6, %7, %8, %9, %10, %11, %12, %13, %14, %15, %16, %17, %18, %19, %20, %21, %22, %23, %24, %25, %26, %27, %28, %29, %30, %31}, ta, tb, p, 1, 1, %35, %36;\n}\n"
    : "+f"(d[0]), "+f"(d[1]), "+f"(d[2]), "+f"(d[3]), "+f"(d[4]), "+f"(d[5]), "+f"(d[6]), "+f"(d[7]), "+f"(d[8]), "+f"(d[9]), "+f"(d[10]), "+f"(d[11]), "+f"(d[12]), "+f"(d[13]), "+f"(d[14]), "+f"(d[15]), "+f"(d[16]), "+f"(d[17]), "+f"(d[18]), "+f"(d[19]), "+f"(d[20]), "+f"(d[21]), "+f"(d[22]), "+f"(d[23]), "+f"(d[24]), "+f"(d[25]), "+f"(d[26]), "+f"(d[27]), "+f"(d[28]), "+f"(d[29]), "+f"(d[30]), "+f"(d[31])
    : "l"(da), "l"(db), "r"(scaleD), "n"(TA), "n"(TB), "n"(OA), "n"(OB));
}
template<int TA, int TB, int OA, int OB> __device__ __forceinline__ void wgmma_ss_n128(float* d, uint64_t da, uint64_t db, int scaleD) {
  asm volatile("{\n.reg .pred p;\n.reg .b64 ta, tb;\nsetp.ne.b32 p, %66, 0;\nadd.s64 ta, %64, %69;\nadd.s64 tb, %65, %70;\n"
    "wgmma.mma_async.sync.aligned.m64n128k16.f32.bf16.bf16 {%0, %1, %2, %3, %4, %5, %6, %7, %8, %9, %10, %11, %12, %13, %14, %15, %16, %17, %18, %19, %20, %21, %22, %23, %24, %25, %26, %27, %28, %29, %30, %31, %32, %33, %34, %35, %36, %37, %38, %39, %40, %41, %42, %43, %44, %45, %46, %47, %48, %49, %50, %51, %52, %53, %54, %55, %56, %57, %58, %59, %60, %61, %62, %63}, ta, tb, p, 1, 1, %67, %68;\n}\n"
    : "+f"(d[0]), "+f"(d[1]), "+f"(d[2]), "+f"(d[3]), "+f"(d[4]), "+f"(d[5]), "+f"(d[6]), "+f"(d[7]), "+f"(d[8]), "+f"(d[9]), "+f"(d[10]), "+f"(d[11]), "+f"(d[12]), "+f"(d[13]), "+f"(d[14]), "+f"(d[15]), "+f"(d[16]), "+f"(d[17]), "+f"(d[18]), "+f"(d[19]), "+f"(d[20]), "+f"(d[21]), "+f"(d[22]), "+f"(d[23]), "+f"(d[24]), "+f"(d[25]), "+f"(d[26]), "+f"(d[27]), "+f"(d[28]), "+f"(d[29]), "+f"(d[30]), "+f"(d[31]), "+f"(d[32]), "+f"(d[33]), "+f"(d[34]), "+f"(d[35]), "+f"(d[36]), "+f"(d[37]), "+f"(d[38]), "+f"(d[39]), "+f"(d[40]), "+f"(d[41]), "+f"(d[42]), "+f"(d[43]), "+f"(d[44]), "+f"(d[45]), "+f"(d[46]), "+f"(d[47]), "+f"(d[48]), "+f"(d[49]), "+f"(d[50]), "+f"(d[51]), "+f"(d[52]), "+f"(d[53]), "+f"(d[54]), "+f"(d[55]), "+f"(d[56]), "+f"(d[57]), "+f"(d[58]), "+f"(d[59]), "+f"(d[60]), "+f"(d[61]), "+f"(d[62]), "+f"(d[63])
    : "l"(da), "l"(db), "r"(scaleD), "n"(TA), "n"(TB), "n"(OA), "n"(OB));
}
template<int OB> __device__ __forceinline__ void wgmma_rs_n32(float* d, const uint32_t* a, uint64_t db, int scaleD) {
  asm volatile("{\n.reg .pred p;\n.reg .b64 tb;\nsetp.ne.b32 p, %21, 0;\nadd.s64 tb, %20, %22;\n"
    "wgmma.mma_async.sync.aligned.m64n32k16.f32.bf16.bf16 {%0, %1, %2, %3, %4, %5, %6, %7, %8, %9, %10, %11, %12, %13, %14, %15}, {%16, %17, %18, %19}, tb, p, 1, 1, 0;\n}\n"
    : "+f"(d[0]), "+f"(d[1]), "+f"(d[2]), "+f"(d[3]), "+f"(d[4]), "+f"(d[5]), "+f"(d[6]), "+f"(d[7]), "+f"(d[8]), "+f"(d[9]), "+f"(d[10]), "+f"(d[11]), "+f"(d[12]), "+f"(d[13]), "+f"(d[14]), "+f"(d[15])
    : "r"(a[0]), "r"(a[1]), "r"(a[2]), "r"(a[3]), "l"(db), "r"(scaleD), "n"(OB));
}
template<int OB> __device__ __forceinline__ void wgmma_rs_n64(float* d, const uint32_t* a, uint64_t db, int scaleD) {
  asm volatile("{\n.reg .pred p;\n.reg .b64 tb;\nsetp.ne.b32 p, %37, 0;\nadd.s64 tb, %36, %38;\n"
    "wgmma.mma_async.sync.aligned.m64n64k16.f32.bf16.bf16 {%0, %1, %2, %3, %4, %5, %6, %7, %8, %9, %10, %11, %12, %13, %14, %15, %16, %17, %18, %19, %20, %21, %22, %23, %24, %25, %26, %27, %28, %29, %30, %31}, {%32, %33, %34, %35}, tb, p, 1, 1, 0;\n}\n"
    : "+f"(d[0]), "+f"(d[1]), "+f"(d[2]), "+f"(d[3]), "+f"(d[4]), "+f"(d[5]), "+f"(d[6]), "+f"(d[7]), "+f"(d[8]), "+f"(d[9]), "+f"(d[10]), "+f"(d[11]), "+f"(d[12]), "+f"(d[13]), "+f"(d[14]), "+f"(d[15]), "+f"(d[16]), "+f"(d[17]), "+f"(d[18]), "+f"(d[19]), "+f"(d[20]), "+f"(d[21]), "+f"(d[22]), "+f"(d[23]), "+f"(d[24]), "+f"(d[25]), "+f"(d[26]), "+f"(d[27]), "+f"(d[28]), "+f"(d[29]), "+f"(d[30]), "+f"(d[31])
    : "r"(a[0]), "r"(a[1]), "r"(a[2]), "r"(a[3]), "l"(db), "r"(scaleD), "n"(OB));
}
template<int OB> __device__ __forceinline__ void wgmma_rs_n96(float* d, const uint32_t* a, uint64_t db, int scaleD) {
  asm volatile("{\n.reg .pred p;\n.reg .b64 tb;\nsetp.ne.b32 p, %53, 0;\nadd.s64 tb, %52, %54;\n"
    "wgmma.mma_async.sync.aligned.m64n96k16.f32.bf16.bf16 {%0, %1, %2, %3, %4, %5, %6, %7, %8, %9, %10, %11, %12, %13, %14, %15, %16, %17, %18, %19, %20, %21, %22, %23, %24, %25, %26, %27, %28, %29, %30, %31, %32, %33, %34, %35, %36, %37, %38, %39, %40, %41, %42, %43, %44, %45, %46, %47}, {%48, %49, %50, %51}, tb, p, 1, 1, 0;\n}\n"
    : "+f"(d[0]), "+f"(d[1]), "+f"(d[2]), "+f"(d[3]), "+f"(d[4]), "+f"(d[5]), "+f"(d[6]), "+f"(d[7]), "+f"(d[8]), "+f"(d[9]), "+f"(d[10]), "+f"(d[11]), "+f"(d[12]), "+f"(d[13]), "+f"(d[14]), "+f"(d[15]), "+f"(d[16]), "+f"(d[17]), "+f"(d[18]), "+f"(d[19]), "+f"(d[20]), "+f"(d[21]), "+f"(d[22]), "+f"(d[23]), "+f"(d[24]), "+f"(d[25]), "+f"(d[26]), "+f"(d[27]), "+f"(d[28]), "+f"(d[29]), "+f"(d[30]), "+f"(d[31]), "+f"(d[32]), "+f"(d[33]), "+f"(d[34]), "+f"(d[35]), "+f"(d[36]), "+f"(d[37]), "+f"(d[38]), "+f"(d[39]), "+f"(d[40]), "+f"(d[41]), "+f"(d[42]), "+f"(d[43]), "+f"(d[44]), "+f"(d[45]), "+f"(d[46]), "+f"(d[47])
    : "r"(a[0]), "r"(a[1]), "r"(a[2]), "r"(a[3]), "l"(db), "r"(scaleD), "n"(OB));
}
template<int OB> __device__ __forceinline__ void wgmma_rs_n128(float* d, const uint32_t* a, uint64_t db, int scaleD) {
  asm volatile("{\n.reg .pred p;\n.reg .b64 tb;\nsetp.ne.b32 p, %69, 0;\nadd.s64 tb, %68, %70;\n"
    "wgmma.mma_async.sync.aligned.m64n128k16.f32.bf16.bf16 {%0, %1, %2, %3, %4, %5, %6, %7, %8, %9, %10, %11, %12, %13, %14, %15, %16, %17, %18, %19, %20, %21, %22, %23, %24, %25, %26, %27, %28, %29, %30, %31, %32, %33, %34, %35, %36, %37, %38, %39, %40, %41, %42, %43, %44, %45, %46, %47, %48, %49, %50, %51, %52, %53, %54, %55, %56, %57, %58, %59, %60, %61, %62, %63}, {%64, %65, %66, %67}, tb, p, 1, 1, 0;\n}\n"
    : "+f"(d[0]), "+f"(d[1]), "+f"(d[2]), "+f"(d[3]), "+f"(d[4]), "+f"(d[5]), "+f"(d[6]), "+f"(d[7]), "+f"(d[8]), "+f"(d[9]), "+f"(d[10]), "+f"(d[11]), "+f"(d[12]), "+f"(d[13]), "+f"(d[14]), "+f"(d[15]), "+f"(d[16]), "+f"(d[17]), "+f"(d[18]), "+f"(d[19]), "+f"(d[20]), "+f"(d[21]), "+f"(d[22]), "+f"(d[23]), "+f"(d[24]), "+f"(d[25]), "+f"(d[26]), "+f"(d[27]), "+f"(d[28]), "+f"(d[29]), "+f"(d[30]), "+f"(d[31]), "+f"(d[32]), "+f"(d[33]), "+f"(d[34]), "+f"(d[35]), "+f"(d[36]), "+f"(d[37]), "+f"(d[38]), "+f"(d[39]), "+f"(d[40]), "+f"(d[41]), "+f"(d[42]), "+f"(d[43]), "+f"(d[44]), "+f"(d[45]), "+f"(d[46]), "+f"(d[47]), "+f"(d[48]), "+f"(d[49]), "+f"(d[50]), "+f"(d[51]), "+f"(d[52]), "+f"(d[53]), "+f"(d[54]), "+f"(d[55]), "+f"(d[56]), "+f"(d[57]), "+f"(d[58]), "+f"(d[59]), "+f"(d[60]), "+f"(d[61]), "+f"(d[62]), "+f"(d[63])
    : "r"(a[0]), "r"(a[1]), "r"(a[2]), "r"(a[3]), "l"(db), "r"(scaleD), "n"(OB));
}
template<int N, int OB> __device__ __forceinline__ void wgmma_rs(float* d, const uint32_t* a, uint64_t db, int s) {
  if constexpr (N == 32) wgmma_rs_n32<OB>(d, a, db, s);
  if constexpr (N == 64) wgmma_rs_n64<OB>(d, a, db, s);
  if constexpr (N == 96) wgmma_rs_n96<OB>(d, a, db, s);
  if constexpr (N == 128) wgmma_rs_n128<OB>(d, a, db, s);
}

struct Params {
  const __nv_bfloat16* q;
  const __nv_bfloat16* k;
  const __nv_bfloat16* v;
  const __nv_bfloat16* shift_k;
  const __nv_bfloat16* ssm_k;
  const __nv_bfloat16* ssm_D;
  const __nv_bfloat16* gate_w;
  const __nv_bfloat16* w_down;
  const __nv_bfloat16* w_gate;
  const __nv_bfloat16* w_up;
  int zero;
};

template <int BETA>
__device__ __forceinline__ void conv_batch(float* d, const uint32_t* P, uint64_t du) {
  constexpr int KP = BETA / 2, E0 = 4 * (BETA % 2), N = 128 - 32 * KP;
  wg_fence();
  wgmma_rs<N, 8 - E0>(d, P, du, BETA != 0);
  wgmma_rs<N, 7 - E0>(d, P + 4, du, 1);
  wgmma_rs<N, 6 - E0>(d, P + 8, du, 1);
  wgmma_rs<N, 5 - E0>(d, P + 12, du, 1);
  wg_commit();
}
template <int N>
__device__ __forceinline__ void conv_shrink(float* dst, const float* src, uint32_t zero) {
#pragma unroll
  for (int i = 0; i < N; i++) dst[i] = __uint_as_float(__float_as_uint(src[16 + i]) ^ zero);
}
template <int BETA>
__device__ __forceinline__ void conv_loadP(uint32_t* P, uint32_t addr, uint32_t zero) {
  const uint32_t a = addr + 4 * (512 * (BETA / 2) + 64 * (BETA % 2));
  P[2] = lds32v(a);
#pragma unroll
  for (int e = 0; e < 4; e++) {
    P[4 * e] = lds32v(a + 64 * e + 32);
    P[4 * e + 1] = lds32v(a + 64 * e + 64);
  }
#pragma unroll
  for (int e = 0; e < 4; e++) {
    P[4 * e + 3] = P[4 * e] ^ zero;
    if (e > 0) P[4 * e + 2] = P[4 * e - 3] ^ zero;
  }
}

struct HRow { uint4 a, b; uint32_t pa, pb, dD; };
__device__ __forceinline__ void load_hrow(HRow& h, const Params& p, int c, int t) {
  const __nv_bfloat16* hrow = p.ssm_k + (size_t)c * S_LEN;
  h.a = __ldg(reinterpret_cast<const uint4*>(hrow) + t);
  h.b = __ldg(reinterpret_cast<const uint4*>(hrow) + 128 + t);
  h.pa = t > 0 ? (uint32_t)__ldg(reinterpret_cast<const unsigned short*>(hrow) + 8 * t - 1) : 0u;
  h.pb = (uint32_t)__ldg(reinterpret_cast<const unsigned short*>(hrow) + 1024 + 8 * t - 1);
  h.dD = (uint32_t)__ldg(reinterpret_cast<const unsigned short*>(p.ssm_D) + c) * 0x10001u;
}

__device__ __forceinline__ void conv_channel(uint8_t* smem, uint32_t sb, uint32_t off_pr, uint32_t off_red, uint32_t off_u, uint32_t bar_u,
                                             int nb, const HRow& h, int c, uint32_t zero, int tri) {
  const int t = threadIdx.x & 127, warp = __shfl_sync(0xffffffffu, t >> 5, 0), lane = t & 31;
  const int rho = lane >> 2, qd = lane & 3, mu = lane >> 3, lr = lane & 7;
  TC(10);
  {
    uint4* a0 = reinterpret_cast<uint4*>(smem + off_pr + 64 + 32 * t);
    a0[0] = make_uint4(__byte_perm(h.a.x, h.pa, 0x5410), __byte_perm(h.a.x, h.a.x, 0x1032), __byte_perm(h.a.y, h.a.x, 0x7610), __byte_perm(h.a.y, h.a.y, 0x1032));
    a0[1] = make_uint4(__byte_perm(h.a.z, h.a.y, 0x7610), __byte_perm(h.a.z, h.a.z, 0x1032), __byte_perm(h.a.w, h.a.z, 0x7610), __byte_perm(h.a.w, h.a.w, 0x1032));
    a0[256] = make_uint4(__byte_perm(h.b.x, h.pb, 0x5410), __byte_perm(h.b.x, h.b.x, 0x1032), __byte_perm(h.b.y, h.b.x, 0x7610), __byte_perm(h.b.y, h.b.y, 0x1032));
    a0[257] = make_uint4(__byte_perm(h.b.z, h.b.y, 0x7610), __byte_perm(h.b.z, h.b.z, 0x1032), __byte_perm(h.b.w, h.b.z, 0x7610), __byte_perm(h.b.w, h.b.w, 0x1032));
    if (t < 4) *reinterpret_cast<uint4*>(smem + off_pr + t * 16) = make_uint4(0, 0, 0, 0);
    if (t >= 32 && t < 48) *reinterpret_cast<uint4*>(smem + off_u + ((t >> 3) & 1) * U_PLANE + (t & 7) * 16) = make_uint4(0, 0, 0, 0);
    fence_async_smem();
  }
  TC(11);
  bar_sync(nb, 128);
  const uint32_t pr_thread = sb + off_pr + 4 * (16 + 128 * warp + rho - 2 * qd - 8);
  const uint32_t ubase = sb + off_u + U_PAD;
  const uint64_t du = make_desc(sb + off_u, U_PLANE, 128, 0);
  const uint32_t urow = ubase + (mu & 1) * U_PLANE + (16 * warp + 8 * (mu >> 1) + lr) * 16;
  float4* const red_w = reinterpret_cast<float4*>(smem + off_red + warp * 4096) + warp * 32 + lane;
  const float4* const red_r = reinterpret_cast<const float4*>(smem + off_red) + 2 * warp * 32 + lane;
  uint32_t P0[16], P1[16];
  float dA[64], dB[48], dC[32], dD[16];
  auto reduce = [&](int rd) {
    uint32_t uf[4], zf[4];
    ldsm_x4_t(uf[0], uf[1], uf[2], uf[3], urow + rd * 1024);
#pragma unroll
    for (int j2 = 0; j2 < 2; j2++) {
      float4 acc = red_r[j2 * 32];
#pragma unroll
      for (int w = 1; w < 4; w++) {
        float4 tt = red_r[w * 256 + j2 * 32];
        if (rd == 0 && 2 * warp + j2 < w) tt = make_float4(0.f, 0.f, 0.f, 0.f);
        acc.x += tt.x; acc.y += tt.y; acc.z += tt.z; acc.w += tt.w;
      }
      zf[2 * j2] = add2(pack2(acc.x, acc.y), mul2(uf[2 * j2], h.dD));
      zf[2 * j2 + 1] = add2(pack2(acc.z, acc.w), mul2(uf[2 * j2 + 1], h.dD));
    }
    __syncwarp();
    stsm_x4_t(sb + off_red + warp * 1024 + (8 * (mu >> 1) + lr) * 32 + (mu & 1) * 16, zf[0], zf[1], zf[2], zf[3]);
    __syncwarp();
    const uint4 zv = *reinterpret_cast<const uint4*>(smem + off_red + warp * 1024 + lane * 16);
    reinterpret_cast<uint4*>(g_zT + (size_t)c * S_LEN)[128 * rd + 32 * warp + lane] = zv;
  };
  auto put = [&](int rd, int jj, const float* v) {
    if (jj + warp >= 8 * rd && jj + warp < 8 * rd + 8) red_w[(jj - 8 * rd) * 32] = make_float4(v[0], v[1], v[2], v[3]);
  };
  conv_loadP<0>(P0, pr_thread, zero);
  conv_loadP<1>(P1, pr_thread, zero);
  TC(12);
  mbar_wait(bar_u, 0);
  TR(tri);
  conv_batch<0>(dA, P0, du);
  conv_batch<1>(dA, P1, du);
  TC(13);
  wg_wait<1>(); conv_loadP<2>(P0, pr_thread, zero);
  TC(14);
  wg_wait<0>(); conv_shrink<48>(dB, dA, zero);
  TC(15);
  conv_batch<2>(dB, P0, du);
  conv_loadP<3>(P1, pr_thread, zero);
  conv_batch<3>(dB, P1, du);
  TC(16);
#pragma unroll
  for (int jj = 0; jj < 4; jj++) put(0, jj, dA + 4 * jj);
  wg_wait<1>(); conv_loadP<4>(P0, pr_thread, zero);
  wg_wait<0>(); conv_shrink<32>(dC, dB, zero);
  TC(17);
  conv_batch<4>(dC, P0, du);
  conv_loadP<5>(P1, pr_thread, zero);
  conv_batch<5>(dC, P1, du);
#pragma unroll
  for (int jj = 4; jj < 8; jj++) put(0, jj, dB + 4 * (jj - 4));
  wg_wait<1>(); conv_loadP<6>(P0, pr_thread, zero);
  wg_wait<0>(); conv_shrink<16>(dD, dC, zero);
  TC(18);
  conv_batch<6>(dD, P0, du);
  conv_loadP<7>(P1, pr_thread, zero);
  conv_batch<7>(dD, P1, du);
  TC(19);
  bar_sync(nb, 128);
  reduce(0);
  TC(20);
  wg_wait<0>();
  TR(tri + 1);
  bar_sync(nb, 128);
#pragma unroll
  for (int jj = 5; jj < 8; jj++) put(1, jj, dB + 4 * (jj - 4));
#pragma unroll
  for (int jj = 8; jj < 12; jj++) put(1, jj, dC + 4 * (jj - 8));
#pragma unroll
  for (int jj = 12; jj < 16; jj++) put(1, jj, dD + 4 * (jj - 12));
  TC(21);
  bar_sync(nb, 128);
  reduce(1);
  TR(tri + 2);
}

__device__ __forceinline__ void geglu_store(const float* g, const float* u, int hh, __nv_bfloat16* dst) {
  uint32_t o[4];
#pragma unroll
  for (int i = 0; i < 4; i++) o[i] = geglu2(g[4 * i + 2 * hh], g[4 * i + 2 * hh + 1], u[4 * i + 2 * hh], u[4 * i + 2 * hh + 1]);
  *reinterpret_cast<uint4*>(dst) = make_uint4(o[0], o[1], o[2], o[3]);
}

constexpr int NB_CONS = 1, NB_WG2 = 2, NB_GA = 3, NB_WG0 = 4  , NB_PUBH = 6  , NB_PUBC = 9  ;

template <int SWAP>
__global__ void __cluster_dims__(2, 1, 1) __launch_bounds__(512, 1)
fused_kernel(const __grid_constant__ CUtensorMap tmX, const __grid_constant__ CUtensorMap tmW2, const __grid_constant__ CUtensorMap tmWr,
             const __grid_constant__ CUtensorMap tmH, const __grid_constant__ CUtensorMap tmWdA, const __grid_constant__ CUtensorMap tmWdB,
             const __grid_constant__ CUtensorMap tmOut, const __grid_constant__ CUtensorMap tmQ, const __grid_constant__ CUtensorMap tmZ,
             const __grid_constant__ CUtensorMap tmK, const __grid_constant__ CUtensorMap tmV, const Params p) {
  extern __shared__ __align__(1024) uint8_t smem[];
  const uint32_t sb = smem_u32(smem);
  const int tid = threadIdx.x;
  const int wg = __shfl_sync(0xffffffffu, tid >> 7, 0);
  const int warp = __shfl_sync(0xffffffffu, (tid >> 5) & 3, 0);
  const int lane = tid & 31;
  const int rho = lane >> 2, qd = lane & 3;
  const int bid = blockIdx.x;
  const int r = bid >> 3, s = bid & 7;
  const int cj = s & 1, sig = s >> 1;
  const int c_first = 4 * bid;

  const uint32_t bar_x = sb + OFF_BAR, bar_wf = bar_x + 64, bar_we = bar_x + 96, bar_full2 = bar_x + 128, bar_empty2 = bar_x + 176;
  const uint32_t bar_u = bar_x + 224  , bar_q = bar_x + 256, bar_pfree = bar_x + 264, bar_xchg = bar_x + 272, bar_kv = bar_x + 280;
  const uint32_t bar_ufree = bar_x + 288, bar_cdone = bar_x + 296, bar_fdone = bar_x + 304, bar_rf = bar_x + 312  , bar_xf = bar_x + 376  ;

  TR(0); TR(1);
  if (tid == 0) {
    if (sb & 1023u) __trap();
    for (int i = 0; i < 8; i++) { mbar_init(bar_x + 8 * i, 1); mbar_init(bar_rf + 8 * i, 1); }
    mbar_init(bar_fdone, 2);
    for (int i = 0; i < 4; i++) { mbar_init(bar_wf + 8 * i, 1); mbar_init(bar_we + 8 * i, 8); mbar_init(bar_u + 8 * i, 1); mbar_init(bar_xf + 8 * i, 8); }
    for (int i = 0; i < (int)NSLOT2; i++) { mbar_init(bar_full2 + 8 * i, 1); mbar_init(bar_empty2 + 8 * i, 8); }
    mbar_init(bar_q, 1); mbar_init(bar_pfree, 8); mbar_init(bar_xchg, 1); mbar_init(bar_kv, 1); mbar_init(bar_ufree, 1); mbar_init(bar_cdone, 8);
    asm volatile("fence.mbarrier_init.release.cluster;" ::: "memory");
    mbar_expect_tx(bar_xchg, 32768);
  }
  __syncthreads();
  asm volatile("barrier.cluster.arrive.release.aligned;" ::: "memory");

  auto load_u = [&](int ch, uint32_t off_u) {
    const __nv_bfloat16* src = g_kvT + (size_t)(c_first + ch) * S_LEN;
    mbar_expect_tx(bar_u + 8 * ch, 4096);
    bulk_g2s(sb + off_u + U_PAD, src, 2048, bar_u + 8 * ch);
    bulk_g2s(sb + off_u + U_PAD + U_PLANE, src + 1024, 2048, bar_u + 8 * ch);
  };

  if (wg == 3) {
    asm volatile("setmaxnreg.dec.sync.aligned.u32 32;");
    if (warp == 0) {
      if (lane == 0) {
        const int n0 = 224 * s, row0 = 128 * r;
#pragma unroll 1
        for (int st = 0; st < 24; st++) {
          const int slot = st & 3;
          const uint32_t fb = bar_wf + 8 * slot;
          if (st >= 4) mbar_wait(bar_we + 8 * slot, ((st >> 2) - 1) & 1);
          const int k0 = 64 * (st & 7);
          if (st < 4) { mbar_expect_tx(bar_x + 8 * st, 16384); tma_2d(sb + st * 16384, &tmX, k0, row0, bar_x + 8 * st); }
          mbar_expect_tx(fb, 16384);
          tma_3d(sb + OFF_W + slot * 16384, &tmW2, n0 + 64 * (st >> 3), k0, 0, fb);
          if (st == 3) {
            for (int j = 4; j < 8; j++) { mbar_expect_tx(bar_x + 8 * j, 16384); tma_2d(sb + j * 16384, &tmX, 64 * j, row0, bar_x + 8 * j); }
          }
        }
#pragma unroll 1
        for (int j = 0; j < 8; j++) {
          if (!(j & 1)) mbar_wait(bar_we + 8 * (j >> 1), 1);
          mbar_expect_tx(bar_rf + 8 * j, 8192);
          tma_3d(sb + OFF_W + j * 8192, &tmWr, n0 + 192, 64 * j, 0, bar_rf + 8 * j);
        }
#pragma unroll 1
        for (int i = 0; i < 14; i++) {
          const int pos = i % 6;
          const int slot = pos < 2 ? pos : (pos < 4 ? pos + 2 : pos - 2);
          const uint32_t sa = sb + slot * SLOT2, fb = bar_full2 + 8 * pos;
          if (i == 0) mbar_wait(bar_xf, 0);
          else if (i == 1) mbar_wait(bar_xf + 8, 0);
          else if (i == 3) mbar_wait(bar_xf + 24, 0);
          else if (i == 4) mbar_wait(bar_cdone, 0);
          else if (i >= 6) mbar_wait(bar_empty2 + 8 * pos, ((i / 6) - 1) & 1);
          const int kap = 2 * i + cj;
          mbar_expect_tx(fb, 32768);
          const CUtensorMap* tw = kap < 24 ? &tmWdA : &tmWdB;
          const int a = kap < 24 ? 7 * (kap & 7) + 2 * (kap >> 3) : 2 * (kap - 24);
          tma_5d(sa + 16384, tw, 128 * sig, a, fb);
          tma_5d(sa + 24576, tw, 128 * sig + 64, a, fb);
          if (i == 0) { flag_wait(FL_A + r, 8); fence_async_all(); }
          if (i == 8) { flag_wait(FL_B + r, 8); fence_async_all(); }
          tma_2d(sa, &tmH, 64 * kap, row0, fb);
        }
        mbar_wait(bar_fdone, 0);
        const unsigned old = atomicAdd(&g_flags[FL_DONE * 8], 1u);
        if (old == NCTA - 1) {
          for (int i = 0; i < FL_COUNT; i++) g_flags[i * 8] = 0u;
        }
      }
    } else if (warp == 1) {
      if (lane == 0) {
        prefetch_tmap(&tmWr); prefetch_tmap(&tmH); prefetch_tmap(&tmWdA); prefetch_tmap(&tmWdB);
        prefetch_tmap(&tmOut); prefetch_tmap(&tmQ); prefetch_tmap(&tmZ);
      }
      bar_sync(NB_PUBH, 288);
      if (lane == 0) { fence_gpu(); flag_add_relaxed(FL_A + r); }
      __syncwarp();
      bar_sync(NB_PUBH + 1, 288);
      if (lane == 0) { fence_gpu(); flag_add_relaxed(FL_B + r); }
      __syncwarp();
      bar_sync(NB_PUBH + 2, 288);
      if (lane == 0) { fence_gpu(); flag_add_relaxed(FL_Z + (c_first >> 6)); }
    } else if (warp == 2) {
      bar_sync(NB_PUBC, 160);
      if (lane == 0) { TRX(19); fence_gpu(); TRX(20); flag_add_relaxed(FL_KV + s); flag_add_relaxed(FL_G + r); }
      __syncwarp();
      bar_sync(NB_PUBC + 1, 160);
      if (lane == 0) { fence_gpu(); flag_add_relaxed(FL_Z + (c_first >> 6)); }
    } else {
      if (lane == 0) {
        const char* wgp = reinterpret_cast<const char*>(p.w_gate) + bid * 1792;
        const char* wup = reinterpret_cast<const char*>(p.w_up) + bid * 1792;
        auto pfw = [&](int sl) { prefetch_l2(wgp + (size_t)sl * (64 * F_DIM * 2), 1792); prefetch_l2(wup + (size_t)sl * (64 * F_DIM * 2), 1792); };
        const long long t0 = clock64();
        auto until = [&](int cyc) { while (clock64() - t0 < cyc) __nanosleep(50); };
        until(PF_KV);
        mbar_expect_tx(bar_kv, 16896 + 16384);
        tma_2d(sb + OFF_PR, &tmK, 64 * s, 128 * r - 4, bar_kv);
        tma_2d(sb + OFF_RED, &tmV, 64 * s, 128 * r, bar_kv);
        until(PF_W);
        pfw(0); pfw(1); pfw(2); pfw(3); pfw(4); pfw(5); pfw(6); pfw(7);
        until(PF_H);
        prefetch_l2(p.ssm_k + (size_t)c_first * S_LEN, 4 * S_LEN * 2);
        until(PF_WD);
        prefetch_l2(reinterpret_cast<const char*>(p.w_down) + (size_t)bid * 14336, 14336);
        flag_wait(FL_KV + (c_first >> 6), 16);
        mbar_wait(bar_ufree, 0);
        TRX(21);
        fence_async_all();
        TRX(22);
        load_u(0, OFF_U);
        load_u(1, OFF_U + U_BUF);
        mbar_wait(bar_xf + 16, 0);
        load_u(2, OFF_CU0);
        load_u(3, OFF_CU1);
      }
    }
    __syncwarp();
    asm volatile("barrier.cluster.wait.acquire.aligned;" ::: "memory");
  } else if (wg == 2) {
    asm volatile("setmaxnreg.inc.sync.aligned.u32 144;");
    const int t2 = tid & 127;
    {
      const uint4 gw0 = __ldg(reinterpret_cast<const uint4*>(p.gate_w) + lane);
      const uint4 gw1 = __ldg(reinterpret_cast<const uint4*>(p.gate_w) + 32 + lane);
      const int grow = 128 * r + 16 * s + 4 * warp;
      uint4 gx0[4], gx1[4];
#pragma unroll
      for (int i = 0; i < 4; i++) {
        const uint4* xp = reinterpret_cast<const uint4*>(p.q + (size_t)(grow + i) * D_DIM);
        gx0[i] = __ldg(xp + lane);
        gx1[i] = __ldg(xp + 32 + lane);
      }
      const int c0 = 64 * s + 2 * lane;
      const uint4 skr = __ldg(reinterpret_cast<const uint4*>(p.shift_k + c0 * 4));
#pragma unroll
      for (int i = 0; i < 4; i++) {
        uint32_t m[8] = {mul2(gx0[i].x, gw0.x), mul2(gx0[i].y, gw0.y), mul2(gx0[i].z, gw0.z), mul2(gx0[i].w, gw0.w),
                         mul2(gx1[i].x, gw1.x), mul2(gx1[i].y, gw1.y), mul2(gx1[i].z, gw1.z), mul2(gx1[i].w, gw1.w)};
        float acc = 0.f;
#pragma unroll
        for (int j = 0; j < 8; j++) acc += lo_f(m[j]) + hi_f(m[j]);
#pragma unroll
        for (int o = 16; o > 0; o >>= 1) acc += __shfl_xor_sync(0xffffffffu, acc, o);
        if (lane == 0) {
          const float sv = __bfloat162float(__float2bfloat16_rn(acc));
          const float gv = 1.0f / (1.0f + __expf(-sv));
          g_gate[grow + i] = __bfloat162float(__float2bfloat16_rn(gv));
        }
      }
      const uint32_t sk0 = __byte_perm(skr.x, skr.z, 0x5410), sk1 = __byte_perm(skr.x, skr.z, 0x7632);
      const uint32_t sk2 = __byte_perm(skr.y, skr.w, 0x5410), sk3 = __byte_perm(skr.y, skr.w, 0x7632);
      TR(3);
      mbar_wait(bar_kv, 0);
      const uint32_t* ks = reinterpret_cast<const uint32_t*>(smem + OFF_PR) + (32 * warp + 1) * 32 + lane;
      const uint32_t* vs = reinterpret_cast<const uint32_t*>(smem + OFF_RED) + (32 * warp) * 32 + lane;
      uint32_t vv[32];
      uint32_t k0 = ks[0], k1 = ks[32], k2 = ks[64];
#pragma unroll
      for (int i = 0; i < 32; i++) {
        const uint32_t k3 = ks[(i + 3) * 32];
        uint32_t a = mul2(k0, sk3);
        a = add2(a, mul2(k1, sk2));
        a = add2(a, mul2(k2, sk1));
        a = add2(a, mul2(k3, sk0));
        vv[i] = mul2(a, vs[i * 32]);
        k0 = k1; k1 = k2; k2 = k3;
      }
      TR(4);
      bar_sync(NB_WG2, 128);
      if (t2 == 0) mbar_arrive(bar_ufree);
      uint4* stg = reinterpret_cast<uint4*>(smem + OFF_RED);
#pragma unroll
      for (int ch = 0; ch < 2; ch++) {
        const uint32_t sel = ch ? 0x7632 : 0x5410;
#pragma unroll
        for (int pl = 0; pl < 2; pl++)
#pragma unroll
          for (int nn = 0; nn < 2; nn++) {
            const int bb = 16 * nn + 8 * pl;
            uint4 o;
            o.x = __byte_perm(vv[bb + 0], vv[bb + 1], sel);
            o.y = __byte_perm(vv[bb + 2], vv[bb + 3], sel);
            o.z = __byte_perm(vv[bb + 4], vv[bb + 5], sel);
            o.w = __byte_perm(vv[bb + 6], vv[bb + 7], sel);
            stg[(2 * lane + ch) * 16 + ((8 * pl + 2 * warp + nn) ^ (lane & 7))] = o;
          }
      }
      bar_sync(NB_WG2, 128);
      {
        const int lc = lane & 15;
#pragma unroll
        for (int i = 0; i < 8; i++) {
          const int ch = 16 * warp + 2 * i + (lane >> 4);
          const uint4 o = stg[ch * 16 + (lc ^ ((ch >> 1) & 7))];
          reinterpret_cast<uint4*>(g_kvT + (size_t)(64 * s + ch) * S_LEN)[(lc >> 3) * 128 + 8 * r + (lc & 7)] = o;
        }
      }
    }
    bar_arrive(NB_PUBC, 160);
    TR(2);
    HRow h0, h1;
    load_hrow(h0, p, c_first, t2);
    load_hrow(h1, p, c_first + 1, t2);
    asm volatile("barrier.cluster.wait.acquire.aligned;" ::: "memory");
    conv_channel(smem, sb, OFF_PR, OFF_RED, OFF_U, bar_u, NB_WG2, h0, c_first, (uint32_t)p.zero, 5);
    conv_channel(smem, sb, OFF_PR, OFF_RED, OFF_U + U_BUF, bar_u + 8, NB_WG2, h1, c_first + 1, (uint32_t)p.zero, 8);
    bar_arrive(NB_PUBC + 1, 160);
    bar_sync(NB_WG2, 128);
    const int mu = lane >> 3, lr = lane & 7;
    if (t2 == 0) {
      fence_async_smem();
      mbar_expect_tx(bar_q, 32768);
      tma_2d(sb + OFF_RED, &tmQ, 128 * sig, 128 * r + 64 * cj, bar_q);
      tma_2d(sb + OFF_RED + 8192, &tmQ, 128 * sig + 64, 128 * r + 64 * cj, bar_q);
      flag_wait(FL_Z + 2 * sig, 32);
      flag_wait(FL_Z + 2 * sig + 1, 32);
      mbar_arrive(bar_fdone);
      fence_async_all();
      tma_2d(sb + OFF_GA, &tmZ, 128 * r + 64 * cj, 128 * sig, bar_q);
    }
    uint32_t* g2s = reinterpret_cast<uint32_t*>(smem + OFF_G2);
    if (warp == 1) {
      if (lane == 0) { flag_wait(FL_G + r, 8); mbar_arrive(bar_fdone); }
      __syncwarp();
      const float2 gg = __ldcg(reinterpret_cast<const float2*>(g_gate + 128 * r + 64 * cj) + lane);
      const uint32_t g2 = pack2(gg.x, gg.y);
      g2s[lane] = g2;
      g2s[32 + lane] = bf2_bits(__hsub2_rn(__floats2bfloat162_rn(1.f, 1.f), bits_bf2(g2)));
    }
    bar_sync(NB_WG2, 128);
    mbar_wait(bar_q, 0);
    TR(17);
    {
      uint32_t z[32];
      const uint32_t zaddr = sb + OFF_GA + (16 * warp + 8 * (mu & 1) + lr) * 128;
#pragma unroll
      for (int jp = 0; jp < 8; jp++)
        ldsm_x4(z[4 * jp], z[4 * jp + 1], z[4 * jp + 2], z[4 * jp + 3], zaddr + (jp >> 2) * 8192 + (((2 * (jp & 3) + (mu >> 1)) ^ lr) << 4));
      __syncwarp();
      const uint32_t qaddr = sb + OFF_RED + (8 * (mu >> 1) + lr) * 128 + (((2 * warp + (mu & 1)) ^ lr) << 4);
#pragma unroll
      for (int jp = 0; jp < 8; jp++) {
        uint32_t qf[4];
        ldsm_x4_t(qf[0], qf[1], qf[2], qf[3], qaddr + jp * 2048);
        const uint32_t ga = g2s[8 * (jp & 3) + qd];
        const uint32_t gb = g2s[8 * (jp & 3) + 4 + qd];
        *reinterpret_cast<uint4*>(smem + OFF_GA + (((jp >> 2) * 4 + warp) * 4 + (jp & 3)) * 512 + lane * 16) =
            make_uint4(mul2(ga, mul2(qf[0], z[4 * jp])), mul2(ga, mul2(qf[1], z[4 * jp + 1])),
                       mul2(gb, mul2(qf[2], z[4 * jp + 2])), mul2(gb, mul2(qf[3], z[4 * jp + 3])));
      }
    }
    TR(18);
    bar_arrive(NB_GA, 384);
  } else {
    asm volatile("setmaxnreg.inc.sync.aligned.u32 168;");
    const int t1 = tid & 127;
    __nv_bfloat16* const hrow = g_h + (size_t)(128 * r + 64 * wg + 16 * warp + rho) * F_DIM + 8 * qd;
    {
      float da[64], db[64];
      const uint64_t dx = make_desc(sb + wg * 8192, 16, 1024, 1), dw = make_desc(sb + OFF_W, 8192, 1024, 1), dw32 = make_desc(sb + OFF_W, 4096, 512, 2);
      auto stage = [&](int st, float* d, bool first) {
        const uint64_t ax = dx + (uint64_t)((st & 7) * 1024), bw = dw + (uint64_t)((st & 3) * 1024);
        mbar_wait(bar_wf + 8 * (st & 3), (st >> 2) & 1);
        wg_fence();
        wgmma_ss_n128<0, 1, 0, 0>(d, ax, bw, !first);
        wgmma_ss_n128<0, 1, 2, 128>(d, ax, bw, 1);
        wgmma_ss_n128<0, 1, 4, 256>(d, ax, bw, 1);
        wgmma_ss_n128<0, 1, 6, 384>(d, ax, bw, 1);
        wg_commit();
        wg_wait<1>();
        if (st > 0 && lane == 0) mbar_arrive(bar_we + 8 * ((st - 1) & 3));
      };
      auto epi = [&](int it, float* d, int col) {
        if (it & 1) {
          const int a = (it >> 1) & 1, hh = it >> 2;
          geglu_store(d + 32 * SWAP + 16 * a, d + 32 * (1 - SWAP) + 16 * a, hh, hrow + (size_t)(8 * hh) * F_DIM + col + 32 * a);
        }
      };
#pragma unroll 1
      for (int it = 0; it < 8; it++) {
        mbar_wait(bar_x + 8 * it, 0);
        if (it < 4) TR(2 + it);
        stage(it, da, it == 0);
      }
      TR(6);
#pragma unroll
      for (int it = 0; it < 8; it++) { stage(8 + it, db, it == 0); epi(it, da, 64 * s); }
      TR(7);
#pragma unroll
      for (int it = 0; it < 8; it++) { stage(16 + it, da, it == 0); epi(it, db, 512 + 64 * s); }
      bar_arrive(NB_PUBH, 288);
      TR(8);
      HRow hc;
      load_hrow(hc, p, c_first + 2 + wg, t1);
      float dc[32];
#pragma unroll
      for (int it = 0; it < 8; it++) {
        const uint64_t ax = dx + (uint64_t)(it * 1024), bw = dw32 + (uint64_t)(it * 512);
        mbar_wait(bar_rf + 8 * it, 0);
        wg_fence();
        wgmma_ss_n64<0, 1, 0, 0>(dc, ax, bw, it != 0);
        wgmma_ss_n64<0, 1, 2, 64>(dc, ax, bw, 1);
        wgmma_ss_n64<0, 1, 4, 128>(dc, ax, bw, 1);
        wgmma_ss_n64<0, 1, 6, 192>(dc, ax, bw, 1);
        wg_commit();
        wg_wait<1>();
        if (lane == 0) {
          if (it == 0) mbar_arrive(bar_we + 24);
          if (it == 2) mbar_arrive(bar_xf);
          if (it == 4) mbar_arrive(bar_xf + 8);
          if (it == 5) mbar_arrive(bar_xf + 16);
        }
        epi(it, da, 1024 + 64 * s);
      }
      wg_wait<0>();
      if (lane == 0) mbar_arrive(bar_xf + 24);
      TR(9);
      geglu_store(dc + 16 * SWAP, dc + 16 * (1 - SWAP), 0, hrow + 1536 + 32 * s);
      geglu_store(dc + 16 * SWAP, dc + 16 * (1 - SWAP), 1, hrow + (size_t)8 * F_DIM + 1536 + 32 * s);
      bar_arrive(NB_PUBH + 1, 288);
      bar_sync(NB_CONS, 256);
      conv_channel(smem, sb, wg ? OFF_CPR1 : OFF_CPR0, wg ? OFF_CRED1 : OFF_CRED0, wg ? OFF_CU1 : OFF_CU0, bar_u + 16 + 8 * wg, NB_WG0 + wg, hc,
                   c_first + 2 + wg, (uint32_t)p.zero, 29);
      bar_arrive(NB_PUBH + 2, 288);
      fence_async_smem();
      __syncwarp();
      if (lane == 0) mbar_arrive(bar_cdone);
    }
    asm volatile("barrier.cluster.wait.acquire.aligned;" ::: "memory");
    {
      float d[64];
      int pos = 0;
      uint32_t ph = 0;
      const uint64_t dA = make_desc(sb + 16384 + wg * 8192, 8192, 1024, 1), dB = make_desc(sb, 16, 1024, 1);
#pragma unroll 1
      for (int it = 0; it < 14; it++) {
        const int slot = pos < 2 ? pos : (pos < 4 ? pos + 2 : pos - 2);
        const uint64_t aa = dA + (uint64_t)(slot * 2048), bb = dB + (uint64_t)(slot * 2048);
        mbar_wait(bar_full2 + 8 * pos, ph);
        TR(10 + it);
        wg_fence();
        wgmma_ss_n128<1, 0, 0, 0>(d, aa, bb, it != 0);
        wgmma_ss_n128<1, 0, 128, 2>(d, aa, bb, 1);
        wgmma_ss_n128<1, 0, 256, 4>(d, aa, bb, 1);
        wgmma_ss_n128<1, 0, 384, 6>(d, aa, bb, 1);
        wg_commit();
        if (it > 0) {
          wg_wait<1>();
          if (lane == 0) {
            if (it <= 8) mbar_arrive(bar_empty2 + 8 * (pos == 0 ? 5 : pos - 1));
            if (it == 9) mbar_arrive_remote(mapa(bar_pfree, cj ^ 1));
          }
        }
        if (++pos == 6) { pos = 0; ph ^= 1; }
      }
      wg_wait<0>();
      TR(24);
      mbar_wait_cluster(bar_pfree, 0);
      {
        const uint32_t xw = mapa(sb + OFF_XCHG + wg * 16384 + t1 * 16, cj ^ 1);
        const uint32_t xb = mapa(bar_xchg, cj ^ 1);
#pragma unroll
        for (int j = 0; j < 8; j++) {
          const float a0 = cj ? d[4 * j] : d[32 + 4 * j], a1 = cj ? d[4 * j + 1] : d[32 + 4 * j + 1];
          const float a2 = cj ? d[4 * j + 2] : d[32 + 4 * j + 2], a3 = cj ? d[4 * j + 3] : d[32 + 4 * j + 3];
          st_async_v4(xw + j * 2048, a0, a1, a2, a3, xb);
        }
#pragma unroll
        for (int j = 0; j < 32; j++) d[j] = cj ? d[32 + j] : d[j];
      }
      bar_sync(NB_GA, 384);
      TR(25);
      mbar_wait_cluster(bar_xchg, 0);
      TR(26);
      {
        const float4* xr = reinterpret_cast<const float4*>(smem + OFF_XCHG + wg * 16384) + t1;
        const uint32_t* g2s = reinterpret_cast<const uint32_t*>(smem + OFF_G2);
        const uint32_t ost = sb + OFF_OST + wg * 8192;
        const int mu = lane >> 3, lr = lane & 7;
        const uint32_t oaddr = ost + (8 * (mu >> 1) + lr) * 128 + (((2 * warp + (mu & 1)) ^ lr) << 4);
#pragma unroll
        for (int jp = 0; jp < 4; jp++) {
          const uint4 ga = *reinterpret_cast<const uint4*>(smem + OFF_GA + ((wg * 4 + warp) * 4 + jp) * 512 + lane * 16);
          uint32_t o[4];
#pragma unroll
          for (int j2 = 0; j2 < 2; j2++) {
            const int j = 2 * jp + j2;
            const float4 x = xr[j * 128];
            const uint32_t om = g2s[32 + 4 * j + qd];
            o[2 * j2] = add2(j2 ? ga.z : ga.x, mul2(om, pack2(d[4 * j] + x.x, d[4 * j + 1] + x.y)));
            o[2 * j2 + 1] = add2(j2 ? ga.w : ga.y, mul2(om, pack2(d[4 * j + 2] + x.z, d[4 * j + 3] + x.w)));
          }
          stsm_x4_t(oaddr + jp * 2048, o[0], o[1], o[2], o[3]);
        }
        fence_async_smem();
        bar_sync(NB_WG0 + wg, 128);
        if (t1 == 0) {
          tma_store_2d(&tmOut, ost, 128 * sig + 64 * wg, 128 * r + 64 * cj);
          asm volatile("cp.async.bulk.commit_group;" ::: "memory");
          asm volatile("cp.async.bulk.wait_group.read 0;" ::: "memory");
        }
        TR(27); TR(28);
      }
    }
  }
}

typedef CUresult (*EncodeFn)(CUtensorMap*, CUtensorMapDataType, cuuint32_t, void*, const cuuint64_t*, const cuuint64_t*, const cuuint32_t*,
                             const cuuint32_t*, CUtensorMapInterleave, CUtensorMapSwizzle, CUtensorMapL2promotion, CUtensorMapFloatOOBfill);

void encode(EncodeFn fn, CUtensorMap* m, const void* base, int rank, const cuuint64_t* dims, const cuuint64_t* strides, const cuuint32_t* box,
            CUtensorMapSwizzle swz) {
  cuuint32_t es[5] = {1, 1, 1, 1, 1};
  fn(m, CU_TENSOR_MAP_DATA_TYPE_BFLOAT16, rank, const_cast<void*>(base), dims, strides, box, es, CU_TENSOR_MAP_INTERLEAVE_NONE, swz,
     CU_TENSOR_MAP_L2_PROMOTION_L2_256B, CU_TENSOR_MAP_FLOAT_OOB_FILL_NONE);
}

}

extern "C" void kernel_launch(void* const* d_in, const int* in_sizes, int n_in, void* d_out, int out_size) {
  (void)in_sizes; (void)n_in; (void)out_size;
  const __nv_bfloat16* q = (const __nv_bfloat16*)d_in[0];
  const __nv_bfloat16* k = (const __nv_bfloat16*)d_in[1];
  const __nv_bfloat16* v = (const __nv_bfloat16*)d_in[2];
  const __nv_bfloat16* shift_k = (const __nv_bfloat16*)d_in[3];
  const __nv_bfloat16* ssm_k = (const __nv_bfloat16*)d_in[4];
  const __nv_bfloat16* ssm_D = (const __nv_bfloat16*)d_in[5];
  const __nv_bfloat16* w_gate = (const __nv_bfloat16*)d_in[7];
  const __nv_bfloat16* w_up = (const __nv_bfloat16*)d_in[8];
  const __nv_bfloat16* w_down = (const __nv_bfloat16*)d_in[9];
  const __nv_bfloat16* gate_w = (const __nv_bfloat16*)d_in[10];

  static EncodeFn fn = nullptr;
  static void* h_ptr = nullptr;
  static void* z_ptr = nullptr;
  if (!fn) {
    cudaDriverEntryPointQueryResult qr;
    void* f = nullptr;
    cudaGetDriverEntryPoint("cuTensorMapEncodeTiled", &f, cudaEnableDefault, &qr);
    fn = (EncodeFn)f;
    cudaGetSymbolAddress(&h_ptr, g_h);
    cudaGetSymbolAddress(&z_ptr, g_zT);
    cudaFuncSetAttribute(fused_kernel<0>, cudaFuncAttributeMaxDynamicSharedMemorySize, SMEM_BYTES);
    cudaFuncSetAttribute(fused_kernel<1>, cudaFuncAttributeMaxDynamicSharedMemorySize, SMEM_BYTES);
  }
  CUtensorMap tmX, tmW2, tmWr, tmH, tmWdA, tmWdB, tmOut, tmQ, tmZ, tmK, tmV;
  {
    cuuint64_t dims[2] = {D_DIM, S_LEN}, str[1] = {D_DIM * 2};
    cuuint32_t box[2] = {64, 128};
    encode(fn, &tmX, q, 2, dims, str, box, CU_TENSOR_MAP_SWIZZLE_128B);
    cuuint32_t boxo[2] = {64, 64};
    encode(fn, &tmOut, d_out, 2, dims, str, boxo, CU_TENSOR_MAP_SWIZZLE_128B);
    encode(fn, &tmQ, q, 2, dims, str, boxo, CU_TENSOR_MAP_SWIZZLE_128B);
    cuuint32_t boxk[2] = {64, 132};
    encode(fn, &tmK, k, 2, dims, str, boxk, CU_TENSOR_MAP_SWIZZLE_NONE);
    encode(fn, &tmV, v, 2, dims, str, box, CU_TENSOR_MAP_SWIZZLE_NONE);
    cuuint64_t dimz[2] = {S_LEN, D_DIM}, strz[1] = {S_LEN * 2};
    encode(fn, &tmZ, z_ptr, 2, dimz, strz, box, CU_TENSOR_MAP_SWIZZLE_128B);
  }
  const bool swapped = (const char*)w_up < (const char*)w_gate;
  {
    const __nv_bfloat16* lo = swapped ? w_up : w_gate;
    const cuuint64_t delta = swapped ? (cuuint64_t)((const char*)w_gate - (const char*)w_up) : (cuuint64_t)((const char*)w_up - (const char*)w_gate);
    cuuint64_t dims[3] = {F_DIM, D_DIM, 2}, str[2] = {F_DIM * 2, delta};
    cuuint32_t box[3] = {64, 64, 2}, boxr[3] = {32, 64, 2};
    encode(fn, &tmW2, lo, 3, dims, str, box, CU_TENSOR_MAP_SWIZZLE_128B);
    encode(fn, &tmWr, lo, 3, dims, str, boxr, CU_TENSOR_MAP_SWIZZLE_64B);
  }
  {
    cuuint64_t dims[2] = {F_DIM, S_LEN}, str[1] = {F_DIM * 2};
    cuuint32_t box[2] = {64, 128};
    encode(fn, &tmH, h_ptr, 2, dims, str, box, CU_TENSOR_MAP_SWIZZLE_128B);
  }
  {
    const cuuint64_t rowb = D_DIM * 2;
    cuuint64_t dims[5] = {D_DIM, 2, 4, 4, 56}, str[4] = {rowb, 8 * rowb, 2 * rowb, 32 * rowb};
    cuuint32_t box[5] = {64, 2, 4, 4, 2};
    encode(fn, &tmWdA, w_down, 5, dims, str, box, CU_TENSOR_MAP_SWIZZLE_128B);
    cuuint64_t dimsB[5] = {D_DIM, 2, 4, 4, 8}, strB[4] = {rowb, 8 * rowb, 2 * rowb, 224 * rowb};
    encode(fn, &tmWdB, w_down + 192 * D_DIM, 5, dimsB, strB, box, CU_TENSOR_MAP_SWIZZLE_128B);
  }
  Params p{q, k, v, shift_k, ssm_k, ssm_D, gate_w, w_down, w_gate, w_up, 0};
  if (swapped) fused_kernel<1><<<NCTA, 512, SMEM_BYTES, cudaStreamPerThread>>>(tmX, tmW2, tmWr, tmH, tmWdA, tmWdB, tmOut, tmQ, tmZ, tmK, tmV, p);
  else fused_kernel<0><<<NCTA, 512, SMEM_BYTES, cudaStreamPerThread>>>(tmX, tmW2, tmWr, tmH, tmWdA, tmWdB, tmOut, tmQ, tmZ, tmK, tmV, p);
}
```

```cpp
#include <cuda_runtime.h>
#include <cuda_bf16.h>
#include <cuda.h>
#include <stdint.h>

namespace {

constexpr int S_LEN = 2048, D_DIM = 512, F_DIM = 1792;
constexpr int NCTA = 128;

__device__ __align__(1024) __nv_bfloat16 g_h[S_LEN * F_DIM];
__device__ __align__(1024) __nv_bfloat16 g_kvT[D_DIM * S_LEN];
__device__ __align__(1024) __nv_bfloat16 g_zT[D_DIM * S_LEN];
__device__ __align__(1024) float g_gate[S_LEN];
constexpr int FL_STRIDE = 64;
constexpr int FL_KV = 0, FL_Z = 8, FL_G = 16, FL_A = 32, FL_B = 48, FL_C = 64, FL_DONE = 80, FL_COUNT = 81;
__device__ __align__(1024) unsigned int g_flags[FL_COUNT * FL_STRIDE];

constexpr uint32_t OFF_W = 131072;
constexpr uint32_t SLOT2 = 32768, NSLOT2 = 5;
constexpr uint32_t U_PLANE = 2176, U_BUF = 4352, U_PAD = 128;
constexpr uint32_t OFF_RED = 196608;
constexpr uint32_t OFF_PR = OFF_RED + 16384;
constexpr uint32_t OFF_U = OFF_PR + 8320;
constexpr uint32_t OFF_GA = OFF_PR;
constexpr uint32_t OFF_G2 = OFF_U + 2 * U_BUF;
constexpr uint32_t OFF_BAR = OFF_G2 + 512;
constexpr uint32_t SMEM_BYTES = OFF_BAR + 448;
constexpr uint32_t OFF_CU0 = 65536, OFF_CPR0 = OFF_CU0 + U_BUF, OFF_CRED0 = 81920;
constexpr uint32_t OFF_XCHG = 2 * SLOT2;
constexpr uint32_t OFF_OST = 0;
static_assert(SMEM_BYTES <= 232448, "smem");

constexpr int PF_KV = 800, PF_H = 6000, PF_W = 6000, PF_WD = 12000;
constexpr int POLL_NS = 60;
constexpr int SPIN_LIMIT = 1 << 21;

__device__ __forceinline__ uint32_t smem_u32(const void* p) { return (uint32_t)__cvta_generic_to_shared(p); }
__device__ __forceinline__ uint64_t make_desc(uint32_t addr, uint32_t lbo, uint32_t sbo, uint32_t swz) {
  return (uint64_t)((addr & 0x3FFFF) >> 4) | ((uint64_t)(lbo >> 4) << 16) | ((uint64_t)(sbo >> 4) << 32) | ((uint64_t)swz << 62);
}
__device__ __forceinline__ void wg_fence() { asm volatile("wgmma.fence.sync.aligned;" ::: "memory"); }
__device__ __forceinline__ void wg_commit() { asm volatile("wgmma.commit_group.sync.aligned;" ::: "memory"); }
template <int N> __device__ __forceinline__ void wg_wait() { asm volatile("wgmma.wait_group.sync.aligned %0;" ::"n"(N) : "memory"); }
__device__ __forceinline__ void mbar_init(uint32_t bar, int cnt) { asm volatile("mbarrier.init.shared::cta.b64 [%0], %1;" ::"r"(bar), "r"(cnt) : "memory"); }
__device__ __forceinline__ void mbar_expect_tx(uint32_t bar, uint32_t bytes) {
  asm volatile("mbarrier.arrive.expect_tx.shared::cta.b64 _, [%0], %1;" ::"r"(bar), "r"(bytes) : "memory");
}
__device__ __forceinline__ void mbar_arrive(uint32_t bar) { asm volatile("mbarrier.arrive.shared::cta.b64 _, [%0];" ::"r"(bar) : "memory"); }
__device__ __forceinline__ void mbar_wait(uint32_t bar, uint32_t parity) {
  uint32_t ok;
  int it = 0;
  do {
    asm volatile("{\n.reg .pred p;\nmbarrier.try_wait.parity.shared::cta.b64 p, [%1], %2;\nselp.u32 %0, 1, 0, p;\n}\n"
                 : "=r"(ok) : "r"(bar), "r"(parity) : "memory");
  } while (!ok && ++it < SPIN_LIMIT);
}
__device__ __forceinline__ void bar_sync(int id, int n) { asm volatile("bar.sync %0, %1;" ::"r"(id), "r"(n) : "memory"); }
__device__ __forceinline__ void bar_arrive(int id, int n) { asm volatile("bar.arrive %0, %1;" ::"r"(id), "r"(n) : "memory"); }
__device__ __forceinline__ void fence_async_smem() { asm volatile("fence.proxy.async.shared::cta;" ::: "memory"); }
__device__ __forceinline__ void fence_async_all() { asm volatile("fence.proxy.async.global;" ::: "memory"); }
__device__ __forceinline__ void tma_2d(uint32_t dst, const CUtensorMap* m, int c0, int c1, uint32_t bar) {
  asm volatile("cp.async.bulk.tensor.2d.shared::cluster.global.mbarrier::complete_tx::bytes [%0], [%1, {%3, %4}], [%2];"
               ::"r"(dst), "l"(m), "r"(bar), "r"(c0), "r"(c1) : "memory");
}
__device__ __forceinline__ void tma_2d_mc(uint32_t dst, const CUtensorMap* m, int c0, int c1, uint32_t bar, uint16_t mask) {
  asm volatile("cp.async.bulk.tensor.2d.shared::cluster.global.mbarrier::complete_tx::bytes.multicast::cluster [%0], [%1, {%3, %4}], [%2], %5;"
               ::"r"(dst), "l"(m), "r"(bar), "r"(c0), "r"(c1), "h"(mask) : "memory");
}
__device__ __forceinline__ void tma_3d(uint32_t dst, const CUtensorMap* m, int c0, int c1, int c2, uint32_t bar) {
  asm volatile("cp.async.bulk.tensor.3d.shared::cluster.global.mbarrier::complete_tx::bytes [%0], [%1, {%3, %4, %5}], [%2];"
               ::"r"(dst), "l"(m), "r"(bar), "r"(c0), "r"(c1), "r"(c2) : "memory");
}
__device__ __forceinline__ void tma_5d(uint32_t dst, const CUtensorMap* m, int c0, int c4, uint32_t bar) {
  asm volatile("cp.async.bulk.tensor.5d.shared::cluster.global.mbarrier::complete_tx::bytes [%0], [%1, {%3, %4, %4, %4, %5}], [%2];"
               ::"r"(dst), "l"(m), "r"(bar), "r"(c0), "r"(0), "r"(c4) : "memory");
}
__device__ __forceinline__ void tma_store_2d(const CUtensorMap* m, uint32_t src, int c0, int c1) {
  asm volatile("cp.async.bulk.tensor.2d.global.shared::cta.bulk_group [%0, {%2, %3}], [%1];" ::"l"(m), "r"(src), "r"(c0), "r"(c1) : "memory");
}
__device__ __forceinline__ void bulk_g2s(uint32_t dst, const void* src, uint32_t bytes, uint32_t bar) {
  asm volatile("cp.async.bulk.shared::cluster.global.mbarrier::complete_tx::bytes [%0], [%1], %2, [%3];"
               ::"r"(dst), "l"(src), "r"(bytes), "r"(bar) : "memory");
}
__device__ __forceinline__ void prefetch_l2(const void* src, uint32_t bytes) {
  asm volatile("cp.async.bulk.prefetch.L2.global [%0], %1;" ::"l"(src), "r"(bytes) : "memory");
}
__device__ __forceinline__ uint32_t mapa(uint32_t addr, uint32_t rank) {
  uint32_t r; asm volatile("mapa.shared::cluster.u32 %0, %1, %2;" : "=r"(r) : "r"(addr), "r"(rank)); return r;
}
__device__ __forceinline__ void mbar_arrive_remote(uint32_t bar) {
  asm volatile("mbarrier.arrive.relaxed.cluster.shared::cluster.b64 _, [%0];" ::"r"(bar) : "memory");
}
__device__ __forceinline__ void mbar_wait_cluster(uint32_t bar, uint32_t parity) {
  uint32_t ok;
  int it = 0;
  do {
    asm volatile("{\n.reg .pred p;\nmbarrier.try_wait.parity.acquire.cluster.shared::cta.b64 p, [%1], %2;\nselp.u32 %0, 1, 0, p;\n}\n"
                 : "=r"(ok) : "r"(bar), "r"(parity) : "memory");
  } while (!ok && ++it < SPIN_LIMIT);
}
__device__ __forceinline__ void st_async_v4(uint32_t addr, float x, float y, float z, float w, uint32_t bar) {
  asm volatile("st.async.weak.shared::cluster.mbarrier::complete_tx::bytes.v4.f32 [%0], {%1,%2,%3,%4}, [%5];"
               ::"r"(addr), "f"(x), "f"(y), "f"(z), "f"(w), "r"(bar) : "memory");
}
__device__ __forceinline__ void fence_gpu() { asm volatile("fence.acq_rel.gpu;" ::: "memory"); }
__device__ __forceinline__ void prefetch_tmap(const CUtensorMap* m) { asm volatile("prefetch.tensormap [%0];" ::"l"(m) : "memory"); }
__device__ __forceinline__ void flag_add_relaxed(int idx) {
  asm volatile("red.relaxed.gpu.global.add.u32 [%0], 1;" ::"l"(&g_flags[idx * FL_STRIDE]) : "memory");
}
__device__ __forceinline__ unsigned flag_ld(int idx) {
  unsigned v;
  asm volatile("ld.relaxed.gpu.global.u32 %0, [%1];" : "=r"(v) : "l"(&g_flags[idx * FL_STRIDE]) : "memory");
  return v;
}
__device__ __forceinline__ void flag_wait(int idx, unsigned target) {
  if (flag_ld(idx) >= target) return;
  for (int it = 0; it < SPIN_LIMIT; it++) {
    const unsigned a = flag_ld(idx);
    __nanosleep(POLL_NS);
    const unsigned b = flag_ld(idx);
    __nanosleep(POLL_NS);
    const unsigned c = flag_ld(idx);
    __nanosleep(POLL_NS);
    const unsigned d = flag_ld(idx);
    if (a >= target || b >= target || c >= target || d >= target) break;
  }
}
__device__ __forceinline__ void bulk_s2g(void* dst, uint32_t src, uint32_t bytes) {
  asm volatile("cp.async.bulk.global.shared::cta.bulk_group [%0], [%1], %2;" ::"l"(dst), "r"(src), "r"(bytes) : "memory");
}
__device__ __forceinline__ void tma_store_3d(const CUtensorMap* m, uint32_t src, int c0, int c1, int c2) {
  asm volatile("cp.async.bulk.tensor.3d.global.shared::cta.bulk_group [%0, {%2, %3, %4}], [%1];" ::"l"(m), "r"(src), "r"(c0), "r"(c1), "r"(c2) : "memory");
}
__device__ __forceinline__ void bulk_commit() { asm volatile("cp.async.bulk.commit_group;" ::: "memory"); }
__device__ __forceinline__ void bulk_wait_read() { asm volatile("cp.async.bulk.wait_group.read 0;" ::: "memory"); }
__device__ __forceinline__ void bulk_wait_all() { asm volatile("cp.async.bulk.wait_group 0;" ::: "memory"); }
__device__ __forceinline__ void ldsm_x4_t(uint32_t& r0, uint32_t& r1, uint32_t& r2, uint32_t& r3, uint32_t addr) {
  asm volatile("ldmatrix.sync.aligned.m8n8.x4.trans.shared.b16 {%0,%1,%2,%3}, [%4];" : "=r"(r0), "=r"(r1), "=r"(r2), "=r"(r3) : "r"(addr) : "memory");
}
__device__ __forceinline__ void ldsm_x4(uint32_t& r0, uint32_t& r1, uint32_t& r2, uint32_t& r3, uint32_t addr) {
  asm volatile("ldmatrix.sync.aligned.m8n8.x4.shared.b16 {%0,%1,%2,%3}, [%4];" : "=r"(r0), "=r"(r1), "=r"(r2), "=r"(r3) : "r"(addr) : "memory");
}
__device__ __forceinline__ void stsm_x4_t(uint32_t addr, uint32_t r0, uint32_t r1, uint32_t r2, uint32_t r3) {
  asm volatile("stmatrix.sync.aligned.m8n8.x4.trans.shared.b16 [%0], {%1,%2,%3,%4};" ::"r"(addr), "r"(r0), "r"(r1), "r"(r2), "r"(r3) : "memory");
}
__device__ __forceinline__ uint32_t lds32v(uint32_t a) { uint32_t v; asm volatile("ld.volatile.shared.u32 %0, [%1];" : "=r"(v) : "r"(a) : "memory"); return v; }
__device__ __forceinline__ uint32_t bf2_bits(__nv_bfloat162 v) { return *reinterpret_cast<uint32_t*>(&v); }
__device__ __forceinline__ __nv_bfloat162 bits_bf2(uint32_t v) { return *reinterpret_cast<__nv_bfloat162*>(&v); }
__device__ __forceinline__ uint32_t mul2(uint32_t a, uint32_t b) { return bf2_bits(__hmul2_rn(bits_bf2(a), bits_bf2(b))); }
__device__ __forceinline__ uint32_t add2(uint32_t a, uint32_t b) { return bf2_bits(__hadd2_rn(bits_bf2(a), bits_bf2(b))); }
__device__ __forceinline__ uint32_t pack2(float lo, float hi) { return bf2_bits(__floats2bfloat162_rn(lo, hi)); }
__device__ __forceinline__ float lo_f(uint32_t v) { return __uint_as_float(v << 16); }
__device__ __forceinline__ float hi_f(uint32_t v) { return __uint_as_float(v & 0xffff0000u); }
__device__ __forceinline__ float tanh_fast(float x) { float y; asm("tanh.approx.f32 %0, %1;" : "=f"(y) : "f"(x)); return y; }
__device__ __forceinline__ float gelu_tanh(float a) {
  float t = tanh_fast(a * fmaf(0.035677408136f, a * a, 0.7978845608f));
  float h = 0.5f * a;
  return fmaf(h, t, h);
}
__device__ __forceinline__ uint32_t geglu2(float g0, float g1, float u0, float u1) {
  uint32_t gb = pack2(g0, g1);
  uint32_t ub = pack2(u0, u1);
  uint32_t gl = pack2(gelu_tanh(lo_f(gb)), gelu_tanh(hi_f(gb)));
  return mul2(gl, ub);
}

template<int TA, int TB, int OA, int OB> __device__ __forceinline__ void wgmma_ss_n64(float* d, uint64_t da, uint64_t db, int scaleD) {
  asm volatile("{\n.reg .pred p;\n.reg .b64 ta, tb;\nsetp.ne.b32 p, %34, 0;\nadd.s64 ta, %32, %37;\nadd.s64 tb, %33, %38;\n"
    "wgmma.mma_async.sync.aligned.m64n64k16.f32.bf16.bf16 {%0, %1, %2, %3, %4, %5, %6, %7, %8, %9, %10, %11, %12, %13, %14, %15, %16, %17, %18, %19, %20, %21, %22, %23, %24, %25, %26, %27, %28, %29, %30, %31}, ta, tb, p, 1, 1, %35, %36;\n}\n"
    : "+f"(d[0]), "+f"(d[1]), "+f"(d[2]), "+f"(d[3]), "+f"(d[4]), "+f"(d[5]), "+f"(d[6]), "+f"(d[7]), "+f"(d[8]), "+f"(d[9]), "+f"(d[10]), "+f"(d[11]), "+f"(d[12]), "+f"(d[13]), "+f"(d[14]), "+f"(d[15]), "+f"(d[16]), "+f"(d[17]), "+f"(d[18]), "+f"(d[19]), "+f"(d[20]), "+f"(d[21]), "+f"(d[22]), "+f"(d[23]), "+f"(d[24]), "+f"(d[25]), "+f"(d[26]), "+f"(d[27]), "+f"(d[28]), "+f"(d[29]), "+f"(d[30]), "+f"(d[31])
    : "l"(da), "l"(db), "r"(scaleD), "n"(TA), "n"(TB), "n"(OA), "n"(OB));
}
template<int TA, int TB, int OA, int OB> __device__ __forceinline__ void wgmma_ss_n128(float* d, uint64_t da, uint64_t db, int scaleD) {
  asm volatile("{\n.reg .pred p;\n.reg .b64 ta, tb;\nsetp.ne.b32 p, %66, 0;\nadd.s64 ta, %64, %69;\nadd.s64 tb, %65, %70;\n"
    "wgmma.mma_async.sync.aligned.m64n128k16.f32.bf16.bf16 {%0, %1, %2, %3, %4, %5, %6, %7, %8, %9, %10, %11, %12, %13, %14, %15, %16, %17, %18, %19, %20, %21, %22, %23, %24, %25, %26, %27, %28, %29, %30, %31, %32, %33, %34, %35, %36, %37, %38, %39, %40, %41, %42, %43, %44, %45, %46, %47, %48, %49, %50, %51, %52, %53, %54, %55, %56, %57, %58, %59, %60, %61, %62, %63}, ta, tb, p, 1, 1, %67, %68;\n}\n"
    : "+f"(d[0]), "+f"(d[1]), "+f"(d[2]), "+f"(d[3]), "+f"(d[4]), "+f"(d[5]), "+f"(d[6]), "+f"(d[7]), "+f"(d[8]), "+f"(d[9]), "+f"(d[10]), "+f"(d[11]), "+f"(d[12]), "+f"(d[13]), "+f"(d[14]), "+f"(d[15]), "+f"(d[16]), "+f"(d[17]), "+f"(d[18]), "+f"(d[19]), "+f"(d[20]), "+f"(d[21]), "+f"(d[22]), "+f"(d[23]), "+f"(d[24]), "+f"(d[25]), "+f"(d[26]), "+f"(d[27]), "+f"(d[28]), "+f"(d[29]), "+f"(d[30]), "+f"(d[31]), "+f"(d[32]), "+f"(d[33]), "+f"(d[34]), "+f"(d[35]), "+f"(d[36]), "+f"(d[37]), "+f"(d[38]), "+f"(d[39]), "+f"(d[40]), "+f"(d[41]), "+f"(d[42]), "+f"(d[43]), "+f"(d[44]), "+f"(d[45]), "+f"(d[46]), "+f"(d[47]), "+f"(d[48]), "+f"(d[49]), "+f"(d[50]), "+f"(d[51]), "+f"(d[52]), "+f"(d[53]), "+f"(d[54]), "+f"(d[55]), "+f"(d[56]), "+f"(d[57]), "+f"(d[58]), "+f"(d[59]), "+f"(d[60]), "+f"(d[61]), "+f"(d[62]), "+f"(d[63])
    : "l"(da), "l"(db), "r"(scaleD), "n"(TA), "n"(TB), "n"(OA), "n"(OB));
}
template<int OB> __device__ __forceinline__ void wgmma_rs_n32(float* d, const uint32_t* a, uint64_t db, int scaleD) {
  asm volatile("{\n.reg .pred p;\n.reg .b64 tb;\nsetp.ne.b32 p, %21, 0;\nadd.s64 tb, %20, %22;\n"
    "wgmma.mma_async.sync.aligned.m64n32k16.f32.bf16.bf16 {%0, %1, %2, %3, %4, %5, %6, %7, %8, %9, %10, %11, %12, %13, %14, %15}, {%16, %17, %18, %19}, tb, p, 1, 1, 0;\n}\n"
    : "+f"(d[0]), "+f"(d[1]), "+f"(d[2]), "+f"(d[3]), "+f"(d[4]), "+f"(d[5]), "+f"(d[6]), "+f"(d[7]), "+f"(d[8]), "+f"(d[9]), "+f"(d[10]), "+f"(d[11]), "+f"(d[12]), "+f"(d[13]), "+f"(d[14]), "+f"(d[15])
    : "r"(a[0]), "r"(a[1]), "r"(a[2]), "r"(a[3]), "l"(db), "r"(scaleD), "n"(OB));
}
template<int OB> __device__ __forceinline__ void wgmma_rs_n64(float* d, const uint32_t* a, uint64_t db, int scaleD) {
  asm volatile("{\n.reg .pred p;\n.reg .b64 tb;\nsetp.ne.b32 p, %37, 0;\nadd.s64 tb, %36, %38;\n"
    "wgmma.mma_async.sync.aligned.m64n64k16.f32.bf16.bf16 {%0, %1, %2, %3, %4, %5, %6, %7, %8, %9, %10, %11, %12, %13, %14, %15, %16, %17, %18, %19, %20, %21, %22, %23, %24, %25, %26, %27, %28, %29, %30, %31}, {%32, %33, %34, %35}, tb, p, 1, 1, 0;\n}\n"
    : "+f"(d[0]), "+f"(d[1]), "+f"(d[2]), "+f"(d[3]), "+f"(d[4]), "+f"(d[5]), "+f"(d[6]), "+f"(d[7]), "+f"(d[8]), "+f"(d[9]), "+f"(d[10]), "+f"(d[11]), "+f"(d[12]), "+f"(d[13]), "+f"(d[14]), "+f"(d[15]), "+f"(d[16]), "+f"(d[17]), "+f"(d[18]), "+f"(d[19]), "+f"(d[20]), "+f"(d[21]), "+f"(d[22]), "+f"(d[23]), "+f"(d[24]), "+f"(d[25]), "+f"(d[26]), "+f"(d[27]), "+f"(d[28]), "+f"(d[29]), "+f"(d[30]), "+f"(d[31])
    : "r"(a[0]), "r"(a[1]), "r"(a[2]), "r"(a[3]), "l"(db), "r"(scaleD), "n"(OB));
}
template<int OB> __device__ __forceinline__ void wgmma_rs_n96(float* d, const uint32_t* a, uint64_t db, int scaleD) {
  asm volatile("{\n.reg .pred p;\n.reg .b64 tb;\nsetp.ne.b32 p, %53, 0;\nadd.s64 tb, %52, %54;\n"
    "wgmma.mma_async.sync.aligned.m64n96k16.f32.bf16.bf16 {%0, %1, %2, %3, %4, %5, %6, %7, %8, %9, %10, %11, %12, %13, %14, %15, %16, %17, %18, %19, %20, %21, %22, %23, %24, %25, %26, %27, %28, %29, %30, %31, %32, %33, %34, %35, %36, %37, %38, %39, %40, %41, %42, %43, %44, %45, %46, %47}, {%48, %49, %50, %51}, tb, p, 1, 1, 0;\n}\n"
    : "+f"(d[0]), "+f"(d[1]), "+f"(d[2]), "+f"(d[3]), "+f"(d[4]), "+f"(d[5]), "+f"(d[6]), "+f"(d[7]), "+f"(d[8]), "+f"(d[9]), "+f"(d[10]), "+f"(d[11]), "+f"(d[12]), "+f"(d[13]), "+f"(d[14]), "+f"(d[15]), "+f"(d[16]), "+f"(d[17]), "+f"(d[18]), "+f"(d[19]), "+f"(d[20]), "+f"(d[21]), "+f"(d[22]), "+f"(d[23]), "+f"(d[24]), "+f"(d[25]), "+f"(d[26]), "+f"(d[27]), "+f"(d[28]), "+f"(d[29]), "+f"(d[30]), "+f"(d[31]), "+f"(d[32]), "+f"(d[33]), "+f"(d[34]), "+f"(d[35]), "+f"(d[36]), "+f"(d[37]), "+f"(d[38]), "+f"(d[39]), "+f"(d[40]), "+f"(d[41]), "+f"(d[42]), "+f"(d[43]), "+f"(d[44]), "+f"(d[45]), "+f"(d[46]), "+f"(d[47])
    : "r"(a[0]), "r"(a[1]), "r"(a[2]), "r"(a[3]), "l"(db), "r"(scaleD), "n"(OB));
}
template<int OB> __device__ __forceinline__ void wgmma_rs_n128(float* d, const uint32_t* a, uint64_t db, int scaleD) {
  asm volatile("{\n.reg .pred p;\n.reg .b64 tb;\nsetp.ne.b32 p, %69, 0;\nadd.s64 tb, %68, %70;\n"
    "wgmma.mma_async.sync.aligned.m64n128k16.f32.bf16.bf16 {%0, %1, %2, %3, %4, %5, %6, %7, %8, %9, %10, %11, %12, %13, %14, %15, %16, %17, %18, %19, %20, %21, %22, %23, %24, %25, %26, %27, %28, %29, %30, %31, %32, %33, %34, %35, %36, %37, %38, %39, %40, %41, %42, %43, %44, %45, %46, %47, %48, %49, %50, %51, %52, %53, %54, %55, %56, %57, %58, %59, %60, %61, %62, %63}, {%64, %65, %66, %67}, tb, p, 1, 1, 0;\n}\n"
    : "+f"(d[0]), "+f"(d[1]), "+f"(d[2]), "+f"(d[3]), "+f"(d[4]), "+f"(d[5]), "+f"(d[6]), "+f"(d[7]), "+f"(d[8]), "+f"(d[9]), "+f"(d[10]), "+f"(d[11]), "+f"(d[12]), "+f"(d[13]), "+f"(d[14]), "+f"(d[15]), "+f"(d[16]), "+f"(d[17]), "+f"(d[18]), "+f"(d[19]), "+f"(d[20]), "+f"(d[21]), "+f"(d[22]), "+f"(d[23]), "+f"(d[24]), "+f"(d[25]), "+f"(d[26]), "+f"(d[27]), "+f"(d[28]), "+f"(d[29]), "+f"(d[30]), "+f"(d[31]), "+f"(d[32]), "+f"(d[33]), "+f"(d[34]), "+f"(d[35]), "+f"(d[36]), "+f"(d[37]), "+f"(d[38]), "+f"(d[39]), "+f"(d[40]), "+f"(d[41]), "+f"(d[42]), "+f"(d[43]), "+f"(d[44]), "+f"(d[45]), "+f"(d[46]), "+f"(d[47]), "+f"(d[48]), "+f"(d[49]), "+f"(d[50]), "+f"(d[51]), "+f"(d[52]), "+f"(d[53]), "+f"(d[54]), "+f"(d[55]), "+f"(d[56]), "+f"(d[57]), "+f"(d[58]), "+f"(d[59]), "+f"(d[60]), "+f"(d[61]), "+f"(d[62]), "+f"(d[63])
    : "r"(a[0]), "r"(a[1]), "r"(a[2]), "r"(a[3]), "l"(db), "r"(scaleD), "n"(OB));
}
template<int N, int OB> __device__ __forceinline__ void wgmma_rs(float* d, const uint32_t* a, uint64_t db, int s) {
  if constexpr (N == 32) wgmma_rs_n32<OB>(d, a, db, s);
  if constexpr (N == 64) wgmma_rs_n64<OB>(d, a, db, s);
  if constexpr (N == 96) wgmma_rs_n96<OB>(d, a, db, s);
  if constexpr (N == 128) wgmma_rs_n128<OB>(d, a, db, s);
}


struct Params {
  const __nv_bfloat16* q;
  const __nv_bfloat16* k;
  const __nv_bfloat16* v;
  const __nv_bfloat16* shift_k;
  const __nv_bfloat16* ssm_k;
  const __nv_bfloat16* ssm_D;
  const __nv_bfloat16* gate_w;
  const __nv_bfloat16* w_down;
  const __nv_bfloat16* w_gate;
  const __nv_bfloat16* w_up;
  int zero;
};

template <int BETA>
__device__ __forceinline__ void conv_batch(float* d, const uint32_t* P, uint64_t du) {
  constexpr int KP = BETA / 2, E0 = 4 * (BETA % 2), N = 128 - 32 * KP;
  wg_fence();
  wgmma_rs<N, 8 - E0>(d, P, du, BETA != 0);
  wgmma_rs<N, 7 - E0>(d, P + 4, du, 1);
  wgmma_rs<N, 6 - E0>(d, P + 8, du, 1);
  wgmma_rs<N, 5 - E0>(d, P + 12, du, 1);
  wg_commit();
}
template <int N>
__device__ __forceinline__ void conv_shrink(float* dst, const float* src, uint32_t zero) {
#pragma unroll
  for (int i = 0; i < N; i++) dst[i] = __uint_as_float(__float_as_uint(src[16 + i]) ^ zero);
}
template <int BETA>
__device__ __forceinline__ void conv_loadP(uint32_t* P, uint32_t addr, uint32_t zero) {
  const uint32_t a = addr + 4 * (512 * (BETA / 2) + 64 * (BETA % 2));
  P[2] = lds32v(a);
#pragma unroll
  for (int e = 0; e < 4; e++) {
    P[4 * e] = lds32v(a + 64 * e + 32);
    P[4 * e + 1] = lds32v(a + 64 * e + 64);
  }
#pragma unroll
  for (int e = 0; e < 4; e++) {
    P[4 * e + 3] = P[4 * e] ^ zero;
    if (e > 0) P[4 * e + 2] = P[4 * e - 3] ^ zero;
  }
}

struct HRow { uint4 a, b; uint32_t pa, pb, dD; };
__device__ __forceinline__ void load_hrow(HRow& h, const Params& p, int c, int t) {
  const __nv_bfloat16* hrow = p.ssm_k + (size_t)c * S_LEN;
  h.a = __ldg(reinterpret_cast<const uint4*>(hrow) + t);
  h.b = __ldg(reinterpret_cast<const uint4*>(hrow) + 128 + t);
  h.pa = t > 0 ? (uint32_t)__ldg(reinterpret_cast<const unsigned short*>(hrow) + 8 * t - 1) : 0u;
  h.pb = (uint32_t)__ldg(reinterpret_cast<const unsigned short*>(hrow) + 1024 + 8 * t - 1);
  h.dD = (uint32_t)__ldg(reinterpret_cast<const unsigned short*>(p.ssm_D) + c) * 0x10001u;
}

template <int nch>
__device__ __forceinline__ void conv_run(uint8_t* smem, uint32_t sb, uint32_t off_pr, uint32_t off_red, uint32_t off_u, uint32_t bar_u, int nb,
                                         const Params& p, HRow h, int c0, uint32_t bar_first_done) {
  const int t = threadIdx.x & 127, warp = __shfl_sync(0xffffffffu, t >> 5, 0), lane = t & 31;
  const int rho = lane >> 2, qd = lane & 3, mu = lane >> 3, lr = lane & 7;
  const uint32_t zero = (uint32_t)p.zero;
  auto build_pr = [&]() {
    uint4* a0 = reinterpret_cast<uint4*>(smem + off_pr + 64 + 32 * t);
    a0[0] = make_uint4(__byte_perm(h.a.x, h.pa, 0x5410), __byte_perm(h.a.x, h.a.x, 0x1032), __byte_perm(h.a.y, h.a.x, 0x7610), __byte_perm(h.a.y, h.a.y, 0x1032));
    a0[1] = make_uint4(__byte_perm(h.a.z, h.a.y, 0x7610), __byte_perm(h.a.z, h.a.z, 0x1032), __byte_perm(h.a.w, h.a.z, 0x7610), __byte_perm(h.a.w, h.a.w, 0x1032));
    a0[256] = make_uint4(__byte_perm(h.b.x, h.pb, 0x5410), __byte_perm(h.b.x, h.b.x, 0x1032), __byte_perm(h.b.y, h.b.x, 0x7610), __byte_perm(h.b.y, h.b.y, 0x1032));
    a0[257] = make_uint4(__byte_perm(h.b.z, h.b.y, 0x7610), __byte_perm(h.b.z, h.b.z, 0x1032), __byte_perm(h.b.w, h.b.z, 0x7610), __byte_perm(h.b.w, h.b.w, 0x1032));
  };
  const uint32_t pr_thread = sb + off_pr + 4 * (16 + 128 * warp + rho - 2 * qd - 8);
  const uint64_t du0 = make_desc(sb + off_u, U_PLANE, 128, 0);
  const uint32_t urow0 = sb + off_u + U_PAD + (mu & 1) * U_PLANE + (16 * warp + 8 * (mu >> 1) + lr) * 16;
  float4* const red_w = reinterpret_cast<float4*>(smem + off_red + warp * 4096) + warp * 32 + lane;
  const float4* const red_r = reinterpret_cast<const float4*>(smem + off_red) + 2 * warp * 32 + lane;
  uint32_t P0[16], P1[16];
  float dA[64], dB[48], dC[32], dD[16];
  auto reduce = [&](int rd, int i, uint32_t dDv) {
    uint32_t uf[4], zf[4];
    ldsm_x4_t(uf[0], uf[1], uf[2], uf[3], urow0 + (i & 1) * U_BUF + rd * 1024);
#pragma unroll
    for (int j2 = 0; j2 < 2; j2++) {
      float4 acc = red_r[j2 * 32];
#pragma unroll
      for (int w = 1; w < 4; w++) {
        float4 tt = red_r[w * 256 + j2 * 32];
        if (rd == 0 && 2 * warp + j2 < w) tt = make_float4(0.f, 0.f, 0.f, 0.f);
        acc.x += tt.x; acc.y += tt.y; acc.z += tt.z; acc.w += tt.w;
      }
      zf[2 * j2] = add2(pack2(acc.x, acc.y), mul2(uf[2 * j2], dDv));
      zf[2 * j2 + 1] = add2(pack2(acc.z, acc.w), mul2(uf[2 * j2 + 1], dDv));
    }
    __syncwarp();
    stsm_x4_t(sb + off_red + warp * 1024 + (8 * (mu >> 1) + lr) * 32 + (mu & 1) * 16, zf[0], zf[1], zf[2], zf[3]);
    fence_async_smem();
    __syncwarp();
    if (lane == 0) {
      bulk_s2g(g_zT + (size_t)(c0 + i + (i >> 1)) * S_LEN + 1024 * rd + 256 * warp, sb + off_red + warp * 1024, 512);
      bulk_commit();
    }
  };
  auto put = [&](int rd, int jj, const float* v) {
    if (jj + warp >= 8 * rd && jj + warp < 8 * rd + 8) red_w[(jj - 8 * rd) * 32] = make_float4(v[0], v[1], v[2], v[3]);
  };
  auto start = [&](int i) {
    conv_loadP<0>(P0, pr_thread, zero);
    conv_loadP<1>(P1, pr_thread, zero);
    mbar_wait(bar_u + 8 * (i + (i >> 1)), 0);
    const uint64_t du = du0 + (uint64_t)((i & 1) * (U_BUF / 16));
    conv_batch<0>(dA, P0, du);
    conv_batch<1>(dA, P1, du);
  };
  build_pr();
  if (t < 4) *reinterpret_cast<uint4*>(smem + off_pr + t * 16) = make_uint4(0, 0, 0, 0);
  if (t >= 32 && t < (nch > 1 ? 64 : 48)) *reinterpret_cast<uint4*>(smem + off_u + ((t >> 4) & 1) * U_BUF + ((t >> 3) & 1) * U_PLANE + (t & 7) * 16) = make_uint4(0, 0, 0, 0);
  fence_async_smem();
  bar_sync(nb, 128);
  uint32_t dDc = h.dD, dDp = 0;
  start(0);
#pragma unroll
  for (int i = 0; i < nch; i++) {
    const uint64_t du = du0 + (uint64_t)((i & 1) * (U_BUF / 16));
    if (i > 0) {
      bar_sync(nb, 128);
      reduce(1, i - 1, dDp);
    }
    wg_wait<1>(); conv_loadP<2>(P0, pr_thread, zero);
    wg_wait<0>(); conv_loadP<3>(P1, pr_thread, zero); conv_shrink<48>(dB, dA, zero);
    conv_batch<2>(dB, P0, du);
    conv_batch<3>(dB, P1, du);
    if (i + 1 < nch) load_hrow(h, p, c0 + (i + 1) + ((i + 1) >> 1), t);
    if (i > 0) {
      if (lane == 0) { bulk_wait_all(); flag_add_relaxed(FL_Z + (c0 >> 6)); }
      bar_sync(nb, 128);
      if (i == 1 && t == 0) mbar_arrive(bar_first_done);
    }
#pragma unroll
    for (int jj = 0; jj < 4; jj++) put(0, jj, dA + 4 * jj);
    wg_wait<1>(); conv_loadP<4>(P0, pr_thread, zero);
    wg_wait<0>(); conv_loadP<5>(P1, pr_thread, zero); conv_shrink<32>(dC, dB, zero);
    conv_batch<4>(dC, P0, du);
    conv_batch<5>(dC, P1, du);
#pragma unroll
    for (int jj = 4; jj < 8; jj++) put(0, jj, dB + 4 * (jj - 4));
    wg_wait<1>(); conv_loadP<6>(P0, pr_thread, zero);
    wg_wait<0>(); conv_loadP<7>(P1, pr_thread, zero); conv_shrink<16>(dD, dC, zero);
    conv_batch<6>(dD, P0, du);
    conv_batch<7>(dD, P1, du);
    bar_sync(nb, 128);
    if (i + 1 < nch) build_pr();
    reduce(0, i, dDc);
    wg_wait<0>();
    if (lane == 0) bulk_wait_read();
    bar_sync(nb, 128);
#pragma unroll
    for (int jj = 5; jj < 8; jj++) put(1, jj, dB + 4 * (jj - 4));
#pragma unroll
    for (int jj = 8; jj < 12; jj++) put(1, jj, dC + 4 * (jj - 8));
#pragma unroll
    for (int jj = 12; jj < 16; jj++) put(1, jj, dD + 4 * (jj - 12));
    dDp = dDc;
    dDc = h.dD;
    if (i + 1 < nch) start(i + 1);
  }
  bar_sync(nb, 128);
  reduce(1, nch - 1, dDp);
  if (lane == 0) { bulk_wait_all(); flag_add_relaxed(FL_Z + (c0 >> 6)); }
  __syncwarp();
}

__device__ __forceinline__ void geglu_store(const float* g, const float* u, int hh, __nv_bfloat16* dst) {
  uint32_t o[4];
#pragma unroll
  for (int i = 0; i < 4; i++) o[i] = geglu2(g[4 * i + 2 * hh], g[4 * i + 2 * hh + 1], u[4 * i + 2 * hh], u[4 * i + 2 * hh + 1]);
  *reinterpret_cast<uint4*>(dst) = make_uint4(o[0], o[1], o[2], o[3]);
}

constexpr int NB_WG2 = 2, NB_GA = 3, NB_WG0 = 4  , NB_PUBH = 6  , NB_PUBC = 9  ;

template <int SWAP>
__global__ void __cluster_dims__(2, 1, 1) __launch_bounds__(512, 1)
fused_kernel(const __grid_constant__ CUtensorMap tmX, const __grid_constant__ CUtensorMap tmW2, const __grid_constant__ CUtensorMap tmWr,
             const __grid_constant__ CUtensorMap tmWdA, const __grid_constant__ CUtensorMap tmWdB,
             const __grid_constant__ CUtensorMap tmOut, const __grid_constant__ CUtensorMap tmZ,
             const __grid_constant__ CUtensorMap tmK, const __grid_constant__ CUtensorMap tmV, const __grid_constant__ CUtensorMap tmKV,
             const __grid_constant__ CUtensorMap tmX64, const Params p) {
  extern __shared__ __align__(1024) uint8_t smem[];
  const uint32_t sb = smem_u32(smem);
  const int tid = threadIdx.x;
  const int wg = __shfl_sync(0xffffffffu, tid >> 7, 0);
  const int warp = __shfl_sync(0xffffffffu, (tid >> 5) & 3, 0);
  const int lane = tid & 31;
  const int rho = lane >> 2, qd = lane & 3;
  const int bid = blockIdx.x;
  const int r = bid >> 3, s = bid & 7;
  const int cj = s & 1, sig = s >> 1;
  const int c_first = 4 * bid;

  const uint32_t bar_x = sb + OFF_BAR, bar_wf = bar_x + 64, bar_we = bar_x + 96, bar_full2 = bar_x + 128, bar_empty2 = bar_x + 176;
  const uint32_t bar_u = bar_x + 224  , bar_q = bar_x + 256, bar_pfree = bar_x + 264, bar_xchg = bar_x + 272, bar_kv = bar_x + 280;
  const uint32_t bar_ufree = bar_x + 288, bar_fdone = bar_x + 304, bar_xf = bar_x + 376  ;
  const uint32_t bar_c0done = bar_x + 408, bar_x5 = bar_x + 416, bar_g = bar_x + 424, bar_z = bar_x + 432;
  if (tid == 384) {
    if (sb & 1023u) __trap();
    for (int i = 0; i < 8; i++) mbar_init(bar_x + 8 * i, 1);
    mbar_init(bar_fdone, 3);
    for (int i = 0; i < 4; i++) { mbar_init(bar_wf + 8 * i, 1); mbar_init(bar_we + 8 * i, 8); mbar_init(bar_u + 8 * i, 1); mbar_init(bar_xf + 8 * i, 8); }
    for (int i = 0; i < (int)NSLOT2; i++) { mbar_init(bar_full2 + 8 * i, 1); mbar_init(bar_empty2 + 8 * i, 4); }
    mbar_init(bar_q, 1); mbar_init(bar_pfree, 4); mbar_init(bar_xchg, 1); mbar_init(bar_kv, 1); mbar_init(bar_ufree, 1);
    mbar_init(bar_c0done, 1); mbar_init(bar_x5, 8); mbar_init(bar_g, 32); mbar_init(bar_z, 1);
    asm volatile("fence.mbarrier_init.release.cluster;" ::: "memory");
    mbar_expect_tx(bar_xchg, 32768);
    mbar_expect_tx(bar_x, 16384 + 8192);
    tma_2d(sb, &tmX, 0, 128 * r, bar_x);
    tma_3d(sb + OFF_W, &tmWr, 224 * s + 192, 0, 0, bar_x);
  }
  __syncthreads();
  asm volatile("barrier.cluster.arrive.relaxed.aligned;" ::: "memory");

  auto load_u = [&](int ch, uint32_t off_u) {
    const __nv_bfloat16* src = g_kvT + (size_t)(c_first + ch) * S_LEN;
    mbar_expect_tx(bar_u + 8 * ch, 4096);
    bulk_g2s(sb + off_u + U_PAD, src, 2048, bar_u + 8 * ch);
    bulk_g2s(sb + off_u + U_PAD + U_PLANE, src + 1024, 2048, bar_u + 8 * ch);
  };

  if (wg == 3) {
    asm volatile("setmaxnreg.dec.sync.aligned.u32 32;");
    if (warp == 0) {
      asm volatile("barrier.cluster.wait.acquire.aligned;" ::: "memory");
      if (lane == 0) {
        const int n0 = 224 * s, row0 = 128 * r;
#pragma unroll 1
        for (int j = 1; j < 8; j++) {
          mbar_expect_tx(bar_x + 8 * j, 16384 + 8192);
          tma_2d_mc(sb + j * 16384 + cj * 8192, &tmX64, 64 * j, row0 + 64 * cj, bar_x + 8 * j, 3);
          tma_3d(sb + OFF_W + j * 8192, &tmWr, n0 + 192, 64 * j, 0, bar_x + 8 * j);
        }
#pragma unroll 1
        for (int st = 0; st < 24; st++) {
          const int slot = st & 3;
          const uint32_t fb = bar_wf + 8 * slot;
          mbar_wait(bar_we + 8 * slot, (st >> 2) & 1);
          mbar_expect_tx(fb, 16384);
          tma_3d(sb + OFF_W + slot * 16384, &tmW2, n0 + 64 * (st >> 3), 64 * (st & 7), 0, fb);
        }
#pragma unroll 1
        for (int i = 0; i < 14; i++) {
          const int pos = i % 5;
          const int slot = pos < 2 ? pos : pos + 1;
          const uint32_t sa = sb + slot * SLOT2, fb = bar_full2 + 8 * pos;
          if (i == 0) mbar_wait(bar_xf, 0);
          else if (i == 1) mbar_wait(bar_xf + 8, 0);
          else if (i == 2) mbar_wait(bar_xf + 24, 0);
          else if (i >= 5) mbar_wait(bar_empty2 + 8 * pos, ((i / 5) - 1) & 1);
          const int kap = 2 * i + cj;
          mbar_expect_tx(fb, 32768);
          const CUtensorMap* tw = kap < 4 ? &tmWdB : &tmWdA;
          const int a = kap < 4 ? 2 * kap : 7 * ((kap - 4) & 7) + 2 * ((kap - 4) >> 3);
          tma_5d(sa + 16384, tw, 128 * sig, a, fb);
          tma_5d(sa + 24576, tw, 128 * sig + 64, a, fb);
          if (i == 0) { flag_wait(FL_A + r, 8); fence_async_all(); }
          if (i == 6) { flag_wait(FL_B + r, 8); fence_async_all(); }
          if (i == 10) { flag_wait(FL_C + r, 8); fence_async_all(); }
          bulk_g2s(sa, g_h + (size_t)r * (128 * F_DIM) + (size_t)kap * 8192, 16384, fb);
        }
        mbar_wait(bar_fdone, 0);
        const unsigned old = atomicAdd(&g_flags[FL_DONE * FL_STRIDE], 1u);
        if (old == NCTA - 1) {
          for (int i = 0; i < FL_COUNT; i++) g_flags[i * FL_STRIDE] = 0u;
        }
      }
    } else if (warp == 1) {
      if (lane == 0) {
        prefetch_tmap(&tmWr); prefetch_tmap(&tmWdA); prefetch_tmap(&tmWdB);
        prefetch_tmap(&tmOut); prefetch_tmap(&tmZ);
        const char* wgp = reinterpret_cast<const char*>(p.w_gate) + bid * 1792;
        const char* wup = reinterpret_cast<const char*>(p.w_up) + bid * 1792;
        auto pfw = [&](int sl) { prefetch_l2(wgp + (size_t)sl * (64 * F_DIM * 2), 1792); prefetch_l2(wup + (size_t)sl * (64 * F_DIM * 2), 1792); };
        const long long t0 = clock64();
        auto until = [&](int cyc) { while (clock64() - t0 < cyc) __nanosleep(50); };
        until(PF_H);
        prefetch_l2(p.ssm_k + (size_t)c_first * S_LEN, 4 * S_LEN * 2);
        until(PF_W);
        pfw(0); pfw(1); pfw(2); pfw(3); pfw(4); pfw(5); pfw(6); pfw(7);
        until(PF_WD);
        prefetch_l2(reinterpret_cast<const char*>(p.w_down) + (size_t)bid * 14336, 14336);
      }
      __syncwarp();
      bar_sync(NB_PUBH, 288);
      if (lane == 0) { fence_gpu(); flag_add_relaxed(FL_A + r); }
      __syncwarp();
      bar_sync(NB_PUBH + 1, 288);
      if (lane == 0) { fence_gpu(); flag_add_relaxed(FL_B + r); }
      __syncwarp();
      bar_sync(NB_PUBH + 2, 288);
      if (lane == 0) { fence_gpu(); flag_add_relaxed(FL_C + r); }
      __syncwarp();
    } else if (warp == 2) {
      bar_sync(NB_PUBC + 1, 160);
      if (lane == 0) {
        fence_gpu();
        flag_add_relaxed(FL_G + r);
        flag_wait(FL_KV + (c_first >> 6), 16);
        mbar_arrive(bar_fdone);
        fence_async_all();
        flag_wait(FL_G + r, 8);
        mbar_arrive(bar_fdone);
      }
      __syncwarp();
      {
        uint32_t* g2s = reinterpret_cast<uint32_t*>(smem + OFF_G2);
#pragma unroll
        for (int i = 0; i < 2; i++) {
          const float2 gg = __ldcg(reinterpret_cast<const float2*>(g_gate + 128 * r) + 32 * i + lane);
          const uint32_t g2 = pack2(gg.x, gg.y);
          g2s[32 * i + lane] = g2;
          g2s[64 + 32 * i + lane] = bf2_bits(__hsub2_rn(__floats2bfloat162_rn(1.f, 1.f), bits_bf2(g2)));
        }
        mbar_arrive(bar_g);
      }
      if (lane == 0) {
        mbar_wait(bar_x5, 0);
        load_u(2, OFF_CU0);
      }

    } else {
      if (lane == 0) {
        const long long t0 = clock64();
        auto until = [&](int cyc) { while (clock64() - t0 < cyc) __nanosleep(50); };
        until(PF_KV);
        mbar_expect_tx(bar_kv, 16896 + 16384);
        tma_2d(sb + OFF_PR, &tmK, 64 * s, 128 * r - 4, bar_kv);
        tma_2d(sb + OFF_RED, &tmV, 64 * s, 128 * r, bar_kv);
        flag_wait(FL_KV + (c_first >> 6), 16);
        mbar_wait(bar_ufree, 0);
        fence_async_all();
        load_u(0, OFF_U);
        load_u(1, OFF_U + U_BUF);
        mbar_wait(bar_c0done, 0);
        load_u(3, OFF_U);
      }
    }
    __syncwarp();
    if (warp != 0)
    asm volatile("barrier.cluster.wait.acquire.aligned;" ::: "memory");
  } else if (wg == 2) {
    asm volatile("setmaxnreg.inc.sync.aligned.u32 144;");
    const int t2 = tid & 127;
    {
      const uint4 gw0 = __ldg(reinterpret_cast<const uint4*>(p.gate_w) + lane);
      const uint4 gw1 = __ldg(reinterpret_cast<const uint4*>(p.gate_w) + 32 + lane);
      const int grow = 128 * r + 16 * s + 4 * warp;
      uint4 gx0[4], gx1[4];
#pragma unroll
      for (int i = 0; i < 4; i++) {
        const uint4* xp = reinterpret_cast<const uint4*>(p.q + (size_t)(grow + i) * D_DIM);
        gx0[i] = __ldg(xp + lane);
        gx1[i] = __ldg(xp + 32 + lane);
      }
      const int c0 = 64 * s + 2 * lane;
      const uint4 skr = __ldg(reinterpret_cast<const uint4*>(p.shift_k + c0 * 4));
      const uint32_t sk0 = __byte_perm(skr.x, skr.z, 0x5410), sk1 = __byte_perm(skr.x, skr.z, 0x7632);
      const uint32_t sk2 = __byte_perm(skr.y, skr.w, 0x5410), sk3 = __byte_perm(skr.y, skr.w, 0x7632);
      mbar_wait(bar_kv, 0);
      const uint32_t* ks = reinterpret_cast<const uint32_t*>(smem + OFF_PR) + (32 * warp + 1) * 32 + lane;
      const uint32_t* vs = reinterpret_cast<const uint32_t*>(smem + OFF_RED) + (32 * warp) * 32 + lane;
      uint32_t vv[32];
      uint32_t k0 = ks[0], k1 = ks[32], k2 = ks[64];
#pragma unroll
      for (int i = 0; i < 32; i++) {
        const uint32_t k3 = ks[(i + 3) * 32];
        uint32_t a = mul2(k0, sk3);
        a = add2(a, mul2(k1, sk2));
        a = add2(a, mul2(k2, sk1));
        a = add2(a, mul2(k3, sk0));
        vv[i] = mul2(a, vs[i * 32]);
        k0 = k1; k1 = k2; k2 = k3;
      }
      bar_sync(NB_WG2, 128);
      if (t2 == 0) mbar_arrive(bar_ufree);
      uint4* stg = reinterpret_cast<uint4*>(smem + OFF_RED);
#pragma unroll
      for (int ch = 0; ch < 2; ch++) {
        const uint32_t sel = ch ? 0x7632 : 0x5410;
#pragma unroll
        for (int pl = 0; pl < 2; pl++)
#pragma unroll
          for (int nn = 0; nn < 2; nn++) {
            const int bb = 16 * nn + 8 * pl;
            uint4 o;
            o.x = __byte_perm(vv[bb + 0], vv[bb + 1], sel);
            o.y = __byte_perm(vv[bb + 2], vv[bb + 3], sel);
            o.z = __byte_perm(vv[bb + 4], vv[bb + 5], sel);
            o.w = __byte_perm(vv[bb + 6], vv[bb + 7], sel);
            stg[((2 * lane + ch) * 2 + pl) * 8 + ((2 * warp + nn) ^ ((4 * lane + 2 * ch + pl) & 7))] = o;
          }
      }
      fence_async_smem();
      bar_sync(NB_WG2, 128);
      if (t2 == 0) {
        tma_store_3d(&tmKV, sb + OFF_RED, 64 * r, 0, 64 * s);
        bulk_commit();
        bulk_wait_all();
        flag_add_relaxed(FL_KV + s);
      }
      __syncwarp();
      {
        float acc[4];
#pragma unroll
        for (int i = 0; i < 4; i++) {
          uint32_t m[8] = {mul2(gx0[i].x, gw0.x), mul2(gx0[i].y, gw0.y), mul2(gx0[i].z, gw0.z), mul2(gx0[i].w, gw0.w),
                           mul2(gx1[i].x, gw1.x), mul2(gx1[i].y, gw1.y), mul2(gx1[i].z, gw1.z), mul2(gx1[i].w, gw1.w)};
          acc[i] = 0.f;
#pragma unroll
          for (int j = 0; j < 8; j++) acc[i] += lo_f(m[j]) + hi_f(m[j]);
        }
#pragma unroll
        for (int o = 16; o > 0; o >>= 1)
#pragma unroll
          for (int i = 0; i < 4; i++) acc[i] += __shfl_xor_sync(0xffffffffu, acc[i], o);
        const float sel = lane == 0 ? acc[0] : (lane == 1 ? acc[1] : (lane == 2 ? acc[2] : acc[3]));
        if (lane < 4) {
          const float sv = __bfloat162float(__float2bfloat16_rn(sel));
          const float gv = 1.0f / (1.0f + __expf(-sv));
          g_gate[grow + lane] = __bfloat162float(__float2bfloat16_rn(gv));
        }
      }
    }
    bar_arrive(NB_PUBC + 1, 160);
    HRow h0;
    load_hrow(h0, p, c_first, t2);
    asm volatile("barrier.cluster.wait.acquire.aligned;" ::: "memory");
    conv_run<3>(smem, sb, OFF_PR, OFF_RED, OFF_U, bar_u, NB_WG2, p, h0, c_first, bar_c0done);
    bar_sync(NB_WG2, 128);
    const int mu = lane >> 3, lr = lane & 7;
    if (t2 == 0) {
      fence_async_smem();
      mbar_expect_tx(bar_q, 16384);
      tma_2d(sb + OFF_RED, &tmX, 64 * s, 128 * r, bar_q);
      flag_wait(FL_Z + s, 256);
      mbar_arrive(bar_fdone);
      fence_async_all();
      mbar_expect_tx(bar_z, 16384);
      tma_2d(sb + OFF_GA, &tmZ, 128 * r, 64 * s, bar_z);
      tma_2d(sb + OFF_GA + 8192, &tmZ, 128 * r + 64, 64 * s, bar_z);
    }
    __syncwarp();
    {
      const uint32_t* g2s = reinterpret_cast<const uint32_t*>(smem + OFF_G2);
      const uint32_t qaddr = sb + OFF_RED + (8 * (mu >> 1) + lr) * 128 + (((2 * warp + (mu & 1)) ^ lr) << 4);
      uint32_t qf[32], gp[16];
      mbar_wait(bar_g, 0);
#pragma unroll
      for (int j = 0; j < 16; j++) gp[j] = g2s[4 * j + qd];
      mbar_wait(bar_q, 0);
#pragma unroll
      for (int jp = 0; jp < 8; jp++) ldsm_x4_t(qf[4 * jp], qf[4 * jp + 1], qf[4 * jp + 2], qf[4 * jp + 3], qaddr + jp * 2048);
      mbar_wait(bar_z, 0);
      const uint32_t zaddr = sb + OFF_GA + (16 * warp + 8 * (mu & 1) + lr) * 128;
#pragma unroll
      for (int jp = 0; jp < 8; jp++) {
        uint32_t z[4];
        ldsm_x4(z[0], z[1], z[2], z[3], zaddr + (jp >> 2) * 8192 + (((2 * (jp & 3) + (mu >> 1)) ^ lr) << 4));
#pragma unroll
        for (int i = 0; i < 4; i++) qf[4 * jp + i] = mul2(gp[2 * jp + (i >> 1)], mul2(qf[4 * jp + i], z[i]));
      }
      bar_sync(NB_GA, 256);
#pragma unroll
      for (int jp = 0; jp < 8; jp++) {
        const uint4 ob = *reinterpret_cast<const uint4*>(smem + OFF_OST + (jp * 4 + warp) * 512 + lane * 16);
        stsm_x4_t(qaddr + jp * 2048, add2(qf[4 * jp], ob.x), add2(qf[4 * jp + 1], ob.y), add2(qf[4 * jp + 2], ob.z), add2(qf[4 * jp + 3], ob.w));
      }
      fence_async_smem();
      bar_sync(NB_WG2, 128);
      if (t2 == 0) {
        tma_store_2d(&tmOut, sb + OFF_RED, 64 * s, 128 * r);
        tma_store_2d(&tmOut, sb + OFF_RED + 8192, 64 * s, 128 * r + 64);
        bulk_commit();
        bulk_wait_read();
      }
    }
  } else {
    asm volatile("setmaxnreg.inc.sync.aligned.u32 168;");
    const int t1 = tid & 127;
    __nv_bfloat16* const hrow = g_h + (size_t)r * (128 * F_DIM) + (64 * wg + 16 * warp + rho) * 64;
    auto haddr = [&](int col, int hh) {
      return hrow + (size_t)(col >> 6) * 8192 + hh * 512 + (((((col >> 3) & 4) + qd) ^ rho) << 3);
    };
    {
      float da[64], db[64];
      const uint64_t dx = make_desc(sb + wg * 8192, 16, 1024, 1), dw = make_desc(sb + OFF_W, 8192, 1024, 1), dw32 = make_desc(sb + OFF_W, 4096, 512, 2);
      auto stage = [&](int st, float* d, bool first) {
        const uint64_t ax = dx + (uint64_t)((st & 7) * 1024), bw = dw + (uint64_t)((st & 3) * 1024);
        mbar_wait(bar_wf + 8 * (st & 3), (st >> 2) & 1);
        wg_fence();
        wgmma_ss_n128<0, 1, 0, 0>(d, ax, bw, !first);
        wgmma_ss_n128<0, 1, 2, 128>(d, ax, bw, 1);
        wg_commit();
        wg_wait<1>();
        if (lane == 0) {
          if (st < 21) mbar_arrive(bar_we + 8 * ((st - 1) & 3));
          if (st == 18) mbar_arrive(bar_xf);
          if (st == 20) mbar_arrive(bar_xf + 8);
          if (st == 22) mbar_arrive(bar_x5);
        }
        wgmma_ss_n128<0, 1, 4, 256>(d, ax, bw, 1);
        wgmma_ss_n128<0, 1, 6, 384>(d, ax, bw, 1);
        wg_commit();
        wg_wait<1>();
      };
      auto epi = [&](int it, float* d, int col) {
        if (it & 1) {
          const int a = (it >> 1) & 1, hh = it >> 2;
          geglu_store(d + 32 * SWAP + 16 * a, d + 32 * (1 - SWAP) + 16 * a, hh, haddr(col + 32 * a, hh));
        }
      };
      {
        float dc[32];
#pragma unroll 1
        for (int it = 0; it < 8; it++) {
          const uint64_t ax = dx + (uint64_t)(it * 1024), bw = dw32 + (uint64_t)(it * 512);
          mbar_wait(bar_x + 8 * it, 0);
          wg_fence();
          wgmma_ss_n64<0, 1, 0, 0>(dc, ax, bw, it != 0);
          wgmma_ss_n64<0, 1, 2, 64>(dc, ax, bw, 1);
          wgmma_ss_n64<0, 1, 4, 128>(dc, ax, bw, 1);
          wgmma_ss_n64<0, 1, 6, 192>(dc, ax, bw, 1);
          wg_commit();
          wg_wait<1>();
          if (lane == 0 && it >= 2 && !(it & 1)) mbar_arrive(bar_we + 8 * ((it >> 1) - 1));
        }
#pragma unroll
        for (int it = 0; it < 8; it++) {
          stage(it, da, it == 0);
          if (it == 1 || it == 3) geglu_store(dc + 16 * SWAP, dc + 16 * (1 - SWAP), it >> 1, haddr(32 * s, it >> 1));
        }
      }
#pragma unroll
      for (int it = 0; it < 8; it++) { stage(8 + it, db, it == 0); epi(it, da, 256 + 64 * s); }
      bar_arrive(NB_PUBH, 288);
#pragma unroll
      for (int it = 0; it < 8; it++) { stage(16 + it, da, it == 0); epi(it, db, 768 + 64 * s); }
      bar_arrive(NB_PUBH + 1, 288);
      HRow hc;
      if (wg == 0) load_hrow(hc, p, c_first + 2, t1);
      wg_wait<0>();
      if (lane == 0) mbar_arrive(bar_xf + 24);
#pragma unroll
      for (int it = 1; it < 8; it += 2) epi(it, da, 1280 + 64 * s);
      bar_arrive(NB_PUBH + 2, 288);
      asm volatile("barrier.cluster.wait.acquire.aligned;" ::: "memory");
      if (wg == 0) {
        mbar_wait(bar_x5, 0);
        conv_run<1>(smem, sb, OFF_CPR0, OFF_CRED0, OFF_CU0, bar_u + 16, NB_WG0, p, hc, c_first + 2, 0);
        fence_async_smem();
        __syncwarp();
        if (lane == 0) mbar_arrive_remote(mapa(bar_pfree, cj ^ 1));
        return;
      }
    }
    {
      float dk[64], ds[64];
      int pos = 0;
      uint32_t ph = 0;
      const uint64_t dAk = make_desc(sb + 16384 + cj * 8192, 8192, 1024, 1), dAs = make_desc(sb + 16384 + (cj ^ 1) * 8192, 8192, 1024, 1);
      const uint64_t dB = make_desc(sb, 16, 1024, 1);
#pragma unroll 1
      for (int it = 0; it < 14; it++) {
        const int slot = pos < 2 ? pos : pos + 1;
        const uint64_t ak = dAk + (uint64_t)(slot * 2048), as = dAs + (uint64_t)(slot * 2048), bb = dB + (uint64_t)(slot * 2048);
        mbar_wait(bar_full2 + 8 * pos, ph);
        wg_fence();
        wgmma_ss_n128<1, 0, 0, 0>(ds, as, bb, it != 0);
        wgmma_ss_n128<1, 0, 128, 2>(ds, as, bb, 1);
        wg_commit();
        wg_wait<1>();
        if (lane == 0 && it > 0 && it <= 9) mbar_arrive(bar_empty2 + 8 * (pos == 0 ? 4 : pos - 1));
        wgmma_ss_n128<1, 0, 256, 4>(ds, as, bb, 1);
        wgmma_ss_n128<1, 0, 384, 6>(ds, as, bb, 1);
        wg_commit();
        wg_wait<1>();
        wg_fence();
        wgmma_ss_n128<1, 0, 0, 0>(dk, ak, bb, it != 0);
        wgmma_ss_n128<1, 0, 128, 2>(dk, ak, bb, 1);
        wg_commit();
        wg_wait<1>();
        wgmma_ss_n128<1, 0, 256, 4>(dk, ak, bb, 1);
        wgmma_ss_n128<1, 0, 384, 6>(dk, ak, bb, 1);
        wg_commit();
        wg_wait<1>();
        if (++pos == 5) { pos = 0; ph ^= 1; }
      }
      mbar_wait_cluster(bar_pfree, 0);
      wg_wait<1>();
      {
        const uint32_t xw = mapa(sb + OFF_XCHG + t1 * 16, cj ^ 1);
        const uint32_t xb = mapa(bar_xchg, cj ^ 1);
#pragma unroll
        for (int j = 0; j < 16; j++) st_async_v4(xw + j * 2048, ds[4 * j], ds[4 * j + 1], ds[4 * j + 2], ds[4 * j + 3], xb);
      }
      wg_wait<0>();
      {
        const float4* xr = reinterpret_cast<const float4*>(smem + OFF_XCHG) + t1;
        const uint32_t* g2s = reinterpret_cast<const uint32_t*>(smem + OFF_G2);
        uint32_t om[16];
        mbar_wait(bar_g, 0);
#pragma unroll
        for (int j = 0; j < 16; j++) om[j] = g2s[64 + 4 * j + qd];
        mbar_wait_cluster(bar_xchg, 0);
#pragma unroll
        for (int jp = 0; jp < 8; jp++) {
          uint32_t o[4];
#pragma unroll
          for (int j2 = 0; j2 < 2; j2++) {
            const int j = 2 * jp + j2;
            const float4 x = xr[j * 128];
            o[2 * j2] = mul2(om[j], pack2(dk[4 * j] + x.x, dk[4 * j + 1] + x.y));
            o[2 * j2 + 1] = mul2(om[j], pack2(dk[4 * j + 2] + x.z, dk[4 * j + 3] + x.w));
          }
          *reinterpret_cast<uint4*>(smem + OFF_OST + (jp * 4 + warp) * 512 + lane * 16) = make_uint4(o[0], o[1], o[2], o[3]);
        }
        bar_arrive(NB_GA, 256);
      }
    }
  }
}

typedef CUresult (*EncodeFn)(CUtensorMap*, CUtensorMapDataType, cuuint32_t, void*, const cuuint64_t*, const cuuint64_t*, const cuuint32_t*,
                             const cuuint32_t*, CUtensorMapInterleave, CUtensorMapSwizzle, CUtensorMapL2promotion, CUtensorMapFloatOOBfill);

void encode(EncodeFn fn, CUtensorMap* m, const void* base, int rank, const cuuint64_t* dims, const cuuint64_t* strides, const cuuint32_t* box,
            CUtensorMapSwizzle swz) {
  cuuint32_t es[5] = {1, 1, 1, 1, 1};
  fn(m, CU_TENSOR_MAP_DATA_TYPE_BFLOAT16, rank, const_cast<void*>(base), dims, strides, box, es, CU_TENSOR_MAP_INTERLEAVE_NONE, swz,
     CU_TENSOR_MAP_L2_PROMOTION_L2_256B, CU_TENSOR_MAP_FLOAT_OOB_FILL_NONE);
}

}

extern "C" void kernel_launch(void* const* d_in, const int* in_sizes, int n_in, void* d_out, int out_size) {
  (void)in_sizes; (void)n_in; (void)out_size;
  const __nv_bfloat16* q = (const __nv_bfloat16*)d_in[0];
  const __nv_bfloat16* k = (const __nv_bfloat16*)d_in[1];
  const __nv_bfloat16* v = (const __nv_bfloat16*)d_in[2];
  const __nv_bfloat16* shift_k = (const __nv_bfloat16*)d_in[3];
  const __nv_bfloat16* ssm_k = (const __nv_bfloat16*)d_in[4];
  const __nv_bfloat16* ssm_D = (const __nv_bfloat16*)d_in[5];
  const __nv_bfloat16* w_gate = (const __nv_bfloat16*)d_in[7];
  const __nv_bfloat16* w_up = (const __nv_bfloat16*)d_in[8];
  const __nv_bfloat16* w_down = (const __nv_bfloat16*)d_in[9];
  const __nv_bfloat16* gate_w = (const __nv_bfloat16*)d_in[10];

  static EncodeFn fn = nullptr;
  static void* z_ptr = nullptr;
  static void* kv_ptr = nullptr;
  if (!fn) {
    cudaDriverEntryPointQueryResult qr;
    void* f = nullptr;
    cudaGetDriverEntryPoint("cuTensorMapEncodeTiled", &f, cudaEnableDefault, &qr);
    fn = (EncodeFn)f;
    cudaGetSymbolAddress(&z_ptr, g_zT);
    cudaGetSymbolAddress(&kv_ptr, g_kvT);
    cudaFuncSetAttribute(fused_kernel<0>, cudaFuncAttributeMaxDynamicSharedMemorySize, SMEM_BYTES);
    cudaFuncSetAttribute(fused_kernel<1>, cudaFuncAttributeMaxDynamicSharedMemorySize, SMEM_BYTES);
  }
  CUtensorMap tmX, tmW2, tmWr, tmWdA, tmWdB, tmOut, tmZ, tmK, tmV, tmKV, tmX64;
  {
    cuuint64_t dims[2] = {D_DIM, S_LEN}, str[1] = {D_DIM * 2};
    cuuint32_t box[2] = {64, 128};
    encode(fn, &tmX, q, 2, dims, str, box, CU_TENSOR_MAP_SWIZZLE_128B);
    cuuint32_t boxo[2] = {64, 64};
    encode(fn, &tmOut, d_out, 2, dims, str, boxo, CU_TENSOR_MAP_SWIZZLE_128B);
    encode(fn, &tmX64, q, 2, dims, str, boxo, CU_TENSOR_MAP_SWIZZLE_128B);
    cuuint32_t boxk[2] = {64, 132};
    encode(fn, &tmK, k, 2, dims, str, boxk, CU_TENSOR_MAP_SWIZZLE_NONE);
    encode(fn, &tmV, v, 2, dims, str, box, CU_TENSOR_MAP_SWIZZLE_NONE);
    cuuint64_t dimkv[3] = {1024, 2, D_DIM}, strkv[2] = {2048, S_LEN * 2};
    cuuint32_t boxkv[3] = {64, 2, 64};
    encode(fn, &tmKV, kv_ptr, 3, dimkv, strkv, boxkv, CU_TENSOR_MAP_SWIZZLE_128B);
    cuuint64_t dimz[2] = {S_LEN, D_DIM}, strz[1] = {S_LEN * 2};
    encode(fn, &tmZ, z_ptr, 2, dimz, strz, boxo, CU_TENSOR_MAP_SWIZZLE_128B);
  }
  const bool swapped = (const char*)w_up < (const char*)w_gate;
  {
    const __nv_bfloat16* lo = swapped ? w_up : w_gate;
    const cuuint64_t delta = swapped ? (cuuint64_t)((const char*)w_gate - (const char*)w_up) : (cuuint64_t)((const char*)w_up - (const char*)w_gate);
    cuuint64_t dims[3] = {F_DIM, D_DIM, 2}, str[2] = {F_DIM * 2, delta};
    cuuint32_t box[3] = {64, 64, 2}, boxr[3] = {32, 64, 2};
    encode(fn, &tmW2, lo, 3, dims, str, box, CU_TENSOR_MAP_SWIZZLE_128B);
    encode(fn, &tmWr, lo, 3, dims, str, boxr, CU_TENSOR_MAP_SWIZZLE_64B);
  }
  {
    const cuuint64_t rowb = D_DIM * 2;
    cuuint64_t dims[5] = {D_DIM, 2, 4, 4, 56}, str[4] = {rowb, 8 * rowb, 2 * rowb, 32 * rowb};
    cuuint32_t box[5] = {64, 2, 4, 4, 2};
    encode(fn, &tmWdA, w_down, 5, dims, str, box, CU_TENSOR_MAP_SWIZZLE_128B);
    cuuint64_t dimsB[5] = {D_DIM, 2, 4, 4, 8}, strB[4] = {rowb, 8 * rowb, 2 * rowb, 224 * rowb};
    encode(fn, &tmWdB, w_down + 192 * D_DIM, 5, dimsB, strB, box, CU_TENSOR_MAP_SWIZZLE_128B);
  }
  Params p{q, k, v, shift_k, ssm_k, ssm_D, gate_w, w_down, w_gate, w_up, 0};
  if (swapped) fused_kernel<1><<<NCTA, 512, SMEM_BYTES, cudaStreamPerThread>>>(tmX, tmW2, tmWr, tmWdA, tmWdB, tmOut, tmZ, tmK, tmV, tmKV, tmX64, p);
  else fused_kernel<0><<<NCTA, 512, SMEM_BYTES, cudaStreamPerThread>>>(tmX, tmW2, tmWr, tmWdA, tmWdB, tmOut, tmZ, tmK, tmV, tmKV, tmX64, p);
}
```
